```python
import torch

def _softmax(x, axis=-1):
    return torch.softmax(x, dim=axis)
def _gelu(x):
    return torch.nn.functional.gelu(x, approximate="tanh")
def _silu(x):
    return torch.nn.functional.silu(x)
def _sigmoid(x):
    return torch.sigmoid(x)
def _layernorm(x, axis=-1, eps=1e-5):
    m = x.mean(dim=axis, keepdim=True)
    v = x.var(dim=axis, keepdim=True, unbiased=False)
    return (x - m) / torch.sqrt(v + eps)
def _scatter_add(tgt, idx, src, axis=0):
    return tgt.clone().index_add_(axis, idx, src)
def _segment_sum(src, seg, n):
    out = torch.zeros((n,) + src.shape[1:], dtype=src.dtype)
    return out.index_add_(0, seg, src)
def _pad(x, pw):
    flat = tuple(v for pair in reversed(pw) for v in pair)
    return torch.nn.functional.pad(x, flat)

kernel_name = 'concat_heads__gqa_block_cached__mha_block_cached__near_ridge'

def setup_inputs():

    _w = (lambda a: (lambda t: t.to(torch.bfloat16) if t.is_floating_point() else t)(torch.as_tensor(a)))
    def _A_setup():
        B, Sq, D = 16, 48, 512
        Hq, Hkv, Sk, Dh = 32, 8, 512, 128
        assert Hq % Hkv == 0, (Hq, Hkv)
        return {
            "x": _w((lambda *s: torch.randn(*s, dtype=torch.bfloat16) * 0.8)(B, Sq, D)),
            "k_cache": _w((lambda *s: torch.randn(*s, dtype=torch.bfloat16) * 0.8)(B, Hkv, Sk, Dh)),
            "v_cache": _w((lambda *s: torch.randn(*s, dtype=torch.bfloat16) * 0.05)(B, Hkv, Sk, Dh)),
            "wq": _w((lambda *s: torch.randn(*s, dtype=torch.bfloat16) * 0.8)(D, Hq * Dh) * (D ** -0.5)),
            "wo": _w((lambda *s: torch.randn(*s, dtype=torch.bfloat16) * 0.05)(Hq * Dh, D) * ((Hq * Dh) ** -0.5)),
        }
    _A_in = _A_setup()

    def _B_setup():
        B, Sq, D = 16, 48, 512
        H, Sk, Dh = 32, 512, 128
        return {
            "x": _w((lambda *s: torch.randn(*s, dtype=torch.bfloat16) * 0.8)(B, Sq, D)),
            "k_cache": _w((lambda *s: torch.randn(*s, dtype=torch.bfloat16) * 0.8)(B, H, Sk, Dh)),
            "v_cache": _w((lambda *s: torch.randn(*s, dtype=torch.bfloat16) * 0.05)(B, H, Sk, Dh)),
            "wq": _w((lambda *s: torch.randn(*s, dtype=torch.bfloat16) * 0.8)(D, H * Dh) * (D ** -0.5)),
            "wo": _w((lambda *s: torch.randn(*s, dtype=torch.bfloat16) * 0.05)(H * Dh, D) * ((H * Dh) ** -0.5)),
        }
    _B_in = _B_setup()

    return {
        "A_x": _A_in["x"],
        "A_k_cache": _A_in["k_cache"],
        "A_v_cache": _A_in["v_cache"],
        "A_wq": _A_in["wq"],
        "A_wo": _A_in["wo"],
        "B_x": _B_in["x"],
        "B_k_cache": _B_in["k_cache"],
        "B_v_cache": _B_in["v_cache"],
        "B_wq": _B_in["wq"],
        "B_wo": _B_in["wo"],
    }

def reference(A_x, A_k_cache, A_v_cache, A_wq, A_wo, B_x, B_k_cache, B_v_cache, B_wq, B_wo):
    def _A_ref(x, k_cache, v_cache, wq, wo):
        B, Sq, D = x.shape
        Hq, Dh = 32, 128
        Hkv = k_cache.shape[1]
        rep = Hq // Hkv
        q = (lambda x, *d: x.permute(*d))((x @ wq).reshape(B, Sq, Hq, Dh), 0, 2, 1, 3)
        k = (lambda x, n, axis: torch.repeat_interleave(x, n, dim=axis))(k_cache, rep, axis=1)
        v = (lambda x, n, axis: torch.repeat_interleave(x, n, dim=axis))(v_cache, rep, axis=1)
        scores = torch.einsum("bhqd,bhkd->bhqk", q, k) * (Dh ** -0.5)
        p = _softmax(scores, axis=-1)
        o = torch.einsum("bhqk,bhkd->bhqd", p, v)
        return (lambda x, *d: x.permute(*d))(o, 0, 2, 1, 3).reshape(B, Sq, Hq * Dh) @ wo

    def _B_ref(x, k_cache, v_cache, wq, wo):
        B, Sq, D = x.shape
        H, Dh = 32, 128
        q = (lambda x, *d: x.permute(*d))((x @ wq).reshape(B, Sq, H, Dh), 0, 2, 1, 3)
        scores = torch.einsum("bhqd,bhkd->bhqk", q, k_cache) * (Dh ** -0.5)
        p = _softmax(scores, axis=-1)
        o = torch.einsum("bhqk,bhkd->bhqd", p, v_cache)
        return (lambda x, *d: x.permute(*d))(o, 0, 2, 1, 3).reshape(B, Sq, H * Dh) @ wo

    a = _A_ref(A_x, A_k_cache, A_v_cache, A_wq, A_wo)
    b = _B_ref(B_x, B_k_cache, B_v_cache, B_wq, B_wo)
    return torch.concatenate([a, b], axis=-1)
```

```cpp
#include <cuda_runtime.h>
#include <cuda_bf16.h>
#include <cuda.h>
#include <stdint.h>

#define DEVINL __device__ __forceinline__
#define FK_FTK 0
#define FK_TOK 1

namespace fk {

constexpr int kNOproj = 48;
constexpr int kNAttn = 84;
constexpr int kMaxCTA = 160;
constexpr int kSlot = 16384;
constexpr int kRing = 8;
constexpr int kPre = 6;
constexpr int kWarm = 8;
constexpr int kQ1Stage = 40960;
constexpr int kQOff = 6 * kSlot;
constexpr int kQStage = 57344;
constexpr int kBar1a = 200;
constexpr int kBar1b = 128;
constexpr int kOStage = 40960;
constexpr int kNO = 3;
constexpr int kRecvOff = kNO * kOStage;
constexpr int kMergeOff = 10 * kSlot;
constexpr int kSmemBar = 216 * 1024;
constexpr int kMaxUnits = 10;
constexpr int kMaxSeq = 228;

constexpr int kBarFull = 0;
constexpr int kBarEmpty = kMaxSeq;
constexpr int kBarEpoch = 2 * kMaxSeq;
constexpr int kBarP1Done = kBarEpoch + 1;
constexpr int kBarQ0 = kBarP1Done + 1;
constexpr int kBarQStored = kBarQ0 + 3;
constexpr int kBarP1bDone = kBarQStored + 3;
constexpr int kBarRecv = kBarP1bDone + 1;
constexpr int kBarGo = kBarRecv + 1;
constexpr int kBarUnit = kBarGo + kMaxUnits;
constexpr int kBarSig = kBarUnit + kMaxUnits + 1;
constexpr int kNumBars = kBarSig + kMaxUnits;
constexpr int kSmemMisc = kSmemBar + kNumBars * 8;
constexpr int kSmemStats = kSmemMisc + 128;
constexpr int kSmemAck = kSmemStats + 3 * 48 * 8;
constexpr int kSmemTotal = kSmemAck + 384 * 4 + 1024;

struct Maps {
  CUtensorMap kA, vA, kB, vB, xA, xB, wqA, wqB, woA, woB, wqA2, wqB2;
};

__device__ uint4 g_Q[2 * 16 * 32 * 3 * 256];
constexpr int kFlagStride = 32;
constexpr int kFlagQB = 0;
constexpr int kFlagQA = 128;
constexpr int kFlagOA = 160;
constexpr int kFlagOB = 192;
constexpr int kNumFlags = 320;
__device__ unsigned g_flags[kNumFlags * kFlagStride];
__device__ unsigned g_epoch;
__device__ unsigned g_started;
__device__ unsigned g_next;
__device__ unsigned g_sched_done;

#define OTRACE(k, n) do {} while (0)
#define OTRACE1(k, n) do {} while (0)
#define FTRACE(id) do {} while (0)
#define TRACE(role, id) do {} while (0)
#define CTRACE(id) do {} while (0)

DEVINL uint32_t smem_u32(const void* p) { return (uint32_t)__cvta_generic_to_shared(p); }
DEVINL void mbar_init(uint32_t bar, uint32_t cnt) {
  asm volatile("mbarrier.init.shared::cta.b64 [%0], %1;" ::"r"(bar), "r"(cnt) : "memory");
}
DEVINL void mbar_expect_tx(uint32_t bar, uint32_t bytes) {
  asm volatile("mbarrier.arrive.expect_tx.shared::cta.b64 _, [%0], %1;" ::"r"(bar), "r"(bytes) : "memory");
}
DEVINL void mbar_arrive(uint32_t bar, uint32_t cnt) {
  asm volatile("mbarrier.arrive.shared::cta.b64 _, [%0], %1;" ::"r"(bar), "r"(cnt) : "memory");
}
DEVINL bool mbar_try(uint32_t bar, uint32_t parity) {
  uint32_t ok;
  asm volatile(
      "{\n.reg .pred p;\n"
      "mbarrier.try_wait.parity.shared::cta.b64 p, [%1], %2;\n"
      "selp.u32 %0, 1, 0, p;\n}\n"
      : "=r"(ok)
      : "r"(bar), "r"(parity)
      : "memory");
  return ok != 0;
}
DEVINL void mbar_wait(uint32_t bar, uint32_t parity) {
  asm volatile(
      "{\n.reg .pred p;\n.reg .u32 n;\n"
      "mov.u32 n, 0;\n"
      "WAIT_LOOP:\n"
      "mbarrier.try_wait.parity.shared::cta.b64 p, [%0], %1;\n"
      "@p bra WAIT_DONE;\n"
      "add.u32 n, n, 1;\n"
      "setp.lt.u32 p, n, 0x100000;\n"
      "@p bra WAIT_LOOP;\n"
      "WAIT_DONE:\n}\n"
      ::"r"(bar), "r"(parity)
      : "memory");
}
DEVINL void mbar_wait_warp(uint32_t bar, uint32_t parity) {
  asm volatile(
      "{\n.reg .pred p, q;\n.reg .u32 n;\n"
      "mov.u32 n, 0;\n"
      "WAIT_LOOP:\n"
      "mbarrier.try_wait.parity.shared::cta.b64 p, [%0], %1;\n"
      "vote.sync.all.pred q, p, 0xffffffff;\n"
      "@q bra WAIT_DONE;\n"
      "add.u32 n, n, 1;\n"
      "setp.lt.u32 p, n, 0x100000;\n"
      "@p bra WAIT_LOOP;\n"
      "WAIT_DONE:\n}\n"
      ::"r"(bar), "r"(parity)
      : "memory");
}
DEVINL void tma_3d(uint32_t dst, const CUtensorMap* map, uint32_t bar, int c0, int c1, int c2) {
  asm volatile(
      "cp.async.bulk.tensor.3d.shared::cluster.global.mbarrier::complete_tx::bytes [%0], [%1, {%3, %4, %5}], [%2];"
      ::"r"(dst), "l"(map), "r"(bar), "r"(c0), "r"(c1), "r"(c2)
      : "memory");
}
DEVINL void tma_3d_hint(uint32_t dst, const CUtensorMap* map, uint32_t bar, int c0, int c1, int c2, uint64_t pol) {
  asm volatile(
      "cp.async.bulk.tensor.3d.shared::cluster.global.mbarrier::complete_tx::bytes.L2::cache_hint [%0], [%1, {%3, "
      "%4, %5}], [%2], %6;"
      ::"r"(dst), "l"(map), "r"(bar), "r"(c0), "r"(c1), "r"(c2), "l"(pol)
      : "memory");
}
DEVINL void tma_2d(uint32_t dst, const CUtensorMap* map, uint32_t bar, int c0, int c1) {
  asm volatile(
      "cp.async.bulk.tensor.2d.shared::cluster.global.mbarrier::complete_tx::bytes [%0], [%1, {%3, %4}], [%2];"
      ::"r"(dst), "l"(map), "r"(bar), "r"(c0), "r"(c1)
      : "memory");
}
DEVINL void tma_5d(uint32_t dst, const CUtensorMap* map, uint32_t bar, int c0, int c1, int c2, int c3, int c4) {
  asm volatile(
      "cp.async.bulk.tensor.5d.shared::cluster.global.mbarrier::complete_tx::bytes [%0], [%1, {%3, %4, %5, %6, %7}], [%2];"
      ::"r"(dst), "l"(map), "r"(bar), "r"(c0), "r"(c1), "r"(c2), "r"(c3), "r"(c4)
      : "memory");
}
DEVINL void tma_3d_mc(uint32_t dst, const CUtensorMap* map, uint32_t bar, int c0, int c1, int c2, uint16_t mask) {
  asm volatile(
      "cp.async.bulk.tensor.3d.shared::cluster.global.mbarrier::complete_tx::bytes.multicast::cluster [%0], [%1, {%3, "
      "%4, %5}], [%2], %6;"
      ::"r"(dst), "l"(map), "r"(bar), "r"(c0), "r"(c1), "r"(c2), "h"(mask)
      : "memory");
}
DEVINL uint32_t mapa(uint32_t addr, uint32_t rank) {
  uint32_t r;
  asm volatile("mapa.shared::cluster.u32 %0, %1, %2;" : "=r"(r) : "r"(addr), "r"(rank));
  return r;
}
DEVINL void mbar_arrive_remote(uint32_t cluster_addr) {
  asm volatile("mbarrier.arrive.release.cluster.shared::cluster.b64 _, [%0];" ::"r"(cluster_addr) : "memory");
}
DEVINL void cluster_sync() {
  asm volatile("barrier.cluster.arrive.release.aligned;\nbarrier.cluster.wait.acquire.aligned;" ::: "memory");
}
DEVINL void bulk_1d(uint32_t dst, const void* src, uint32_t bytes, uint32_t bar) {
  asm volatile("cp.async.bulk.shared::cluster.global.mbarrier::complete_tx::bytes [%0], [%1], %2, [%3];"
               ::"r"(dst), "l"(src), "r"(bytes), "r"(bar)
               : "memory");
}
DEVINL void prefetch_map(const CUtensorMap* map) {
  asm volatile("prefetch.tensormap [%0];" ::"l"(map) : "memory");
}
DEVINL unsigned ld_acquire(const unsigned* p) {
  unsigned v;
  asm volatile("ld.acquire.gpu.global.u32 %0, [%1];" : "=r"(v) : "l"(p) : "memory");
  return v;
}
DEVINL void wait_flag(const unsigned* p, unsigned target) {
  for (int n = 0; n < (1 << 22); n++) {
    if ((int)(ld_acquire(p) - target) >= 0) break;
  }
}
DEVINL void red_release_add(unsigned* p, unsigned v) {
  asm volatile("red.release.gpu.global.add.u32 [%0], %1;" ::"l"(p), "r"(v) : "memory");
}
DEVINL void bar_sync(int id, int n) { asm volatile("bar.sync %0, %1;" ::"r"(id), "r"(n) : "memory"); }
DEVINL void bar_arrive(int id, int n) { asm volatile("bar.arrive %0, %1;" ::"r"(id), "r"(n) : "memory"); }
DEVINL void fence_proxy_async_global() { asm volatile("fence.proxy.async.global;" ::: "memory"); }

DEVINL void wgmma_fence() { asm volatile("wgmma.fence.sync.aligned;" ::: "memory"); }
DEVINL void wgmma_commit() { asm volatile("wgmma.commit_group.sync.aligned;" ::: "memory"); }
template <int N>
DEVINL void wgmma_wait() {
  asm volatile("wgmma.wait_group.sync.aligned %0;" ::"n"(N) : "memory");
}
template <int N>
DEVINL void fence_regs(float (&d)[N]) {
#pragma unroll
  for (int i = 0; i < N; i++) asm volatile("" : "+f"(d[i])::"memory");
}
template <int N>
DEVINL void fence_regs(uint32_t (&d)[N]) {
#pragma unroll
  for (int i = 0; i < N; i++) asm volatile("" : "+r"(d[i])::"memory");
}

DEVINL uint64_t make_desc(uint32_t addr, uint32_t lbo, uint32_t sbo) {
  return (uint64_t)((addr & 0x3FFFF) >> 4) | ((uint64_t)(lbo >> 4) << 16) | ((uint64_t)(sbo >> 4) << 32) |
         (1ull << 62);
}

#define F8(d, o) "+f"(d[o + 0]), "+f"(d[o + 1]), "+f"(d[o + 2]), "+f"(d[o + 3]), "+f"(d[o + 4]), "+f"(d[o + 5]), "+f"(d[o + 6]), "+f"(d[o + 7])
#define F32(d, o) F8(d, o), F8(d, o + 8), F8(d, o + 16), F8(d, o + 24)
#define R32 "%0, %1, %2, %3, %4, %5, %6, %7, %8, %9, %10, %11, %12, %13, %14, %15, %16, %17, %18, %19, %20, %21, %22, %23, %24, %25, %26, %27, %28, %29, %30, %31"
#define R64 R32 ", %32, %33, %34, %35, %36, %37, %38, %39, %40, %41, %42, %43, %44, %45, %46, %47, %48, %49, %50, %51, %52, %53, %54, %55, %56, %57, %58, %59, %60, %61, %62, %63"

DEVINL void wgmma_ss_n128_tb(float (&d)[64], uint64_t da, uint64_t db, int scale_d) {
  asm volatile(
      "{\n.reg .pred p;\nsetp.ne.b32 p, %66, 0;\n"
      "wgmma.mma_async.sync.aligned.m64n128k16.f32.bf16.bf16 {" R64 "}, %64, %65, p, 1, 1, 0, 1;\n}\n"
      : F32(d, 0), F32(d, 32)
      : "l"(da), "l"(db), "r"(scale_d));
}
DEVINL void wgmma_rs_n128_tb(float (&d)[64], uint32_t a0, uint32_t a1, uint32_t a2, uint32_t a3, uint64_t db,
                             int scale_d) {
  asm volatile(
      "{\n.reg .pred p;\nsetp.ne.b32 p, %69, 0;\n"
      "wgmma.mma_async.sync.aligned.m64n128k16.f32.bf16.bf16 {" R64 "}, {%64, %65, %66, %67}, %68, p, 1, 1, 1;\n}\n"
      : F32(d, 0), F32(d, 32)
      : "r"(a0), "r"(a1), "r"(a2), "r"(a3), "l"(db), "r"(scale_d));
}
DEVINL void wgmma_rs_n64(float (&d)[32], uint32_t a0, uint32_t a1, uint32_t a2, uint32_t a3, uint64_t db,
                         int scale_d) {
  asm volatile(
      "{\n.reg .pred p;\nsetp.ne.b32 p, %37, 0;\n"
      "wgmma.mma_async.sync.aligned.m64n64k16.f32.bf16.bf16 {" R32 "}, {%32, %33, %34, %35}, %36, p, 1, 1, 0;\n}\n"
      : F32(d, 0)
      : "r"(a0), "r"(a1), "r"(a2), "r"(a3), "l"(db), "r"(scale_d));
}

#define O8(d, o) "=f"(d[o + 0]), "=f"(d[o + 1]), "=f"(d[o + 2]), "=f"(d[o + 3]), "=f"(d[o + 4]), "=f"(d[o + 5]), "=f"(d[o + 6]), "=f"(d[o + 7])
#define O32(d, o) O8(d, o), O8(d, o + 8), O8(d, o + 16), O8(d, o + 24)
DEVINL void wgmma_rs_n64_init(float (&d)[32], uint32_t a0, uint32_t a1, uint32_t a2, uint32_t a3, uint64_t db) {
  asm volatile(
      "{\n.reg .pred p;\nsetp.ne.b32 p, %37, 0;\n"
      "wgmma.mma_async.sync.aligned.m64n64k16.f32.bf16.bf16 {" R32 "}, {%32, %33, %34, %35}, %36, p, 1, 1, 0;\n}\n"
      : O32(d, 0)
      : "r"(a0), "r"(a1), "r"(a2), "r"(a3), "l"(db), "r"(0));
}
DEVINL float rcp_approx(float x) {
  float y;
  asm("rcp.approx.ftz.f32 %0, %1;" : "=f"(y) : "f"(x));
  return y;
}

DEVINL uint32_t pack_bf16(float lo, float hi) {
  uint32_t r;
  asm("cvt.rn.bf16x2.f32 %0, %1, %2;" : "=r"(r) : "f"(hi), "f"(lo));
  return r;
}
DEVINL float ex2(float x) {
  float y;
  asm("ex2.approx.ftz.f32 %0, %1;" : "=f"(y) : "f"(x));
  return y;
}

struct Ctx {
  uint32_t sbase;
  int warp;
  int lane;
  int ft;
};
DEVINL uint32_t bar_addr(const Ctx& c, int idx) { return c.sbase + kSmemBar + idx * 8; }

DEVINL void store_frag(uint4* dst, const float* a, int lane) {
#pragma unroll
  for (int j = 0; j < 8; j++)
    dst[j * 32 + lane] = make_uint4(pack_bf16(a[8 * j], a[8 * j + 1]), pack_bf16(a[8 * j + 2], a[8 * j + 3]),
                                    pack_bf16(a[8 * j + 4], a[8 * j + 5]), pack_bf16(a[8 * j + 6], a[8 * j + 7]));
}

DEVINL uint32_t fold_ack(const uint32_t (&a)[8]) { return a[0] ^ a[1] ^ a[2] ^ a[3] ^ a[4] ^ a[5] ^ a[6] ^ a[7]; }

constexpr float kScale = 0.08838834764831845f * 1.4426950408889634f;
DEVINL void attention(const Ctx& c, const uint32_t (&qf)[32], int base, int t0, int tstep, int nturn, int wg, int qbar,
                      uint32_t kv_cnt, uint32_t q_cnt,
                      float (&o)[64], float& m0, float& m1, float& l0, float& l1) {
  float s[32];
  uint32_t pf[16];
  m0 = -INFINITY; m1 = -INFINITY;
  l0 = 0.f; l1 = 0.f;
#pragma unroll
  for (int i = 0; i < 64; i++) o[i] = 0.f;

#pragma unroll 1
  for (int t = t0, turn = 0; turn < nturn; t += tstep, turn++) {
    if (t >= 8) break;
    const int nk = base + 2 * t;
    FTRACE(t * 6 + 0);
    mbar_wait_warp(bar_addr(c, kBarFull + nk), 0);
    FTRACE(t * 6 + 1);
    const uint64_t dk = make_desc(c.sbase + (nk % kRing) * kSlot, 16, 1024);
    wgmma_fence();
    wgmma_rs_n64_init(s, qf[0], qf[1], qf[2], qf[3], dk);
#pragma unroll
    for (int j = 1; j < 8; j++)
      wgmma_rs_n64(s, qf[4 * j], qf[4 * j + 1], qf[4 * j + 2], qf[4 * j + 3], dk + (j >> 2) * 512 + (j & 3) * 2, 1);
    wgmma_commit();
    wgmma_wait<0>();
    fence_regs(s);
    if (c.lane == 0) {
      mbar_arrive(bar_addr(c, kBarEmpty + nk), kv_cnt);
      if (t == t0 && qbar >= 0) mbar_arrive(bar_addr(c, qbar), q_cnt);
    }
    FTRACE(t * 6 + 2);
    if (FK_TOK && tstep == 1) bar_sync(4 + wg, 256);
    fence_regs(s);
    FTRACE(t * 6 + 3);
    uint32_t tok;
    {
      float mx0, mx1;
      {
        float a[8], b[8];
#pragma unroll
        for (int n = 0; n < 8; n++) {
          a[n] = fmaxf(s[4 * n], s[4 * n + 1]);
          b[n] = fmaxf(s[4 * n + 2], s[4 * n + 3]);
        }
#pragma unroll
        for (int w = 4; w >= 1; w >>= 1) {
#pragma unroll
          for (int n = 0; n < w; n++) {
            a[n] = fmaxf(a[n], a[n + w]);
            b[n] = fmaxf(b[n], b[n + w]);
          }
        }
        mx0 = a[0]; mx1 = b[0];
      }
      const bool grow = (mx0 - m0) * kScale > 8.f || (mx1 - m1) * kScale > 8.f;
      if (__any_sync(0xffffffffu, grow)) {
        mx0 = fmaxf(mx0, __shfl_xor_sync(0xffffffffu, mx0, 1));
        mx1 = fmaxf(mx1, __shfl_xor_sync(0xffffffffu, mx1, 1));
        mx0 = fmaxf(mx0, __shfl_xor_sync(0xffffffffu, mx0, 2));
        mx1 = fmaxf(mx1, __shfl_xor_sync(0xffffffffu, mx1, 2));
        const float n0 = fmaxf(m0, mx0), n1 = fmaxf(m1, mx1);
        const float a0 = ex2((m0 - n0) * kScale), a1 = ex2((m1 - n1) * kScale);
        m0 = n0; m1 = n1;
        l0 *= a0; l1 *= a1;
#pragma unroll
        for (int n = 0; n < 16; n++) {
          o[4 * n] *= a0; o[4 * n + 1] *= a0;
          o[4 * n + 2] *= a1; o[4 * n + 3] *= a1;
        }
      }
      const float mn0 = m0, mn1 = m1;
      const float b0 = -mn0 * kScale, b1 = -mn1 * kScale;
      float r0 = 0.f, r1 = 0.f, r2 = 0.f, r3 = 0.f;
#pragma unroll
      for (int n = 0; n < 8; n++) {
        const float p0 = ex2(fmaf(s[4 * n], kScale, b0));
        const float p1 = ex2(fmaf(s[4 * n + 1], kScale, b0));
        const float p2 = ex2(fmaf(s[4 * n + 2], kScale, b1));
        const float p3 = ex2(fmaf(s[4 * n + 3], kScale, b1));
        r0 += p0; r2 += p1;
        r1 += p2; r3 += p3;
        pf[2 * n] = pack_bf16(p0, p1);
        pf[2 * n + 1] = pack_bf16(p2, p3);
      }
      r0 += r2;
      r1 += r3;
      l0 += r0;
      l1 += r1;
      tok = (r0 < 0.f || r1 < 0.f) ? 1u : 0u;
    }
    fence_regs(pf);
    if (FK_TOK && tstep == 1) bar_arrive((wg == 2 ? 4 : 5 + wg) + tok, 256);
    const int nv = nk + 1;
    FTRACE(t * 6 + 4);
    mbar_wait_warp(bar_addr(c, kBarFull + nv), 0);
    const uint64_t dv = make_desc(c.sbase + (nv % kRing) * kSlot, 8192, 1024);
    fence_regs(o);
    fence_regs(pf);
    wgmma_fence();
#pragma unroll
    for (int j = 0; j < 4; j++)
      wgmma_rs_n128_tb(o, pf[4 * j], pf[4 * j + 1], pf[4 * j + 2], pf[4 * j + 3], dv + j * 128, 1);
    wgmma_commit();
    wgmma_wait<0>();
    fence_regs(o);
    fence_regs(pf);
    if (c.lane == 0) mbar_arrive(bar_addr(c, kBarEmpty + nv), kv_cnt);
    FTRACE(t * 6 + 5);
  }
  l0 += __shfl_xor_sync(0xffffffffu, l0, 1);
  l1 += __shfl_xor_sync(0xffffffffu, l1, 1);
  l0 += __shfl_xor_sync(0xffffffffu, l0, 2);
  l1 += __shfl_xor_sync(0xffffffffu, l1, 2);
}

__constant__ unsigned short c_sched[576] = {
    512, 544, 576, 608, 640, 672, 704, 736, 768, 800, 832, 864, 896, 928, 960, 992, 32, 64, 96, 160, 192, 224, 288, 320,
    352, 416, 448, 480, 33, 65, 97, 161, 193, 225, 289, 321, 353, 417, 449, 481, 34, 66, 98, 162, 194, 226, 290, 322,
    354, 418, 450, 482, 513, 545, 577, 609, 641, 673, 705, 737, 769, 801, 833, 865, 897, 929, 961, 993, 35, 67, 99, 163,
    195, 227, 291, 323, 355, 419, 451, 483, 36, 68, 100, 164, 196, 228, 292, 324, 356, 420, 452, 484, 37, 69, 101, 165,
    197, 229, 293, 325, 357, 421, 453, 485, 514, 546, 578, 610, 642, 674, 706, 738, 770, 802, 834, 866, 898, 930, 962, 994,
    38, 70, 102, 166, 198, 230, 294, 326, 358, 422, 454, 486, 39, 71, 103, 167, 199, 231, 295, 327, 359, 423, 455, 487,
    40, 72, 104, 168, 200, 232, 296, 328, 360, 424, 456, 488, 515, 547, 579, 611, 643, 675, 707, 739, 771, 803, 835, 867,
    899, 931, 963, 995, 41, 73, 105, 169, 201, 233, 297, 329, 361, 425, 457, 489, 42, 74, 106, 170, 202, 234, 298, 330,
    362, 426, 458, 490, 43, 75, 107, 171, 203, 235, 299, 331, 363, 427, 459, 491, 516, 548, 580, 612, 644, 676, 708, 740,
    772, 804, 836, 868, 900, 932, 964, 996, 44, 76, 108, 172, 204, 236, 300, 332, 364, 428, 460, 492, 45, 77, 109, 173,
    205, 237, 301, 333, 365, 429, 461, 493, 46, 78, 110, 174, 206, 238, 302, 334, 366, 430, 462, 494, 517, 549, 581, 613,
    645, 677, 709, 741, 773, 805, 837, 869, 901, 933, 965, 997, 47, 79, 111, 175, 207, 239, 303, 335, 367, 431, 463, 495,
    16, 48, 80, 112, 144, 176, 208, 240, 272, 304, 336, 368, 400, 432, 464, 496, 17, 49, 81, 113, 145, 177, 209, 241,
    273, 305, 337, 369, 401, 433, 465, 497, 518, 550, 582, 614, 646, 678, 710, 742, 774, 806, 838, 870, 902, 934, 966, 998,
    18, 50, 82, 114, 146, 178, 210, 242, 274, 306, 338, 370, 402, 434, 466, 498, 19, 51, 83, 115, 147, 179, 211, 243,
    275, 307, 339, 371, 403, 435, 467, 499, 20, 52, 84, 116, 148, 180, 212, 244, 276, 308, 340, 372, 404, 436, 468, 500,
    519, 551, 583, 615, 647, 679, 711, 743, 775, 807, 839, 871, 903, 935, 967, 999, 21, 53, 85, 117, 149, 181, 213, 245,
    277, 309, 341, 373, 405, 437, 469, 501, 22, 54, 86, 118, 150, 182, 214, 246, 278, 310, 342, 374, 406, 438, 470, 502,
    23, 55, 87, 119, 151, 183, 215, 247, 279, 311, 343, 375, 407, 439, 471, 503, 24, 56, 88, 120, 152, 184, 216, 248,
    280, 312, 344, 376, 408, 440, 472, 504, 25, 57, 89, 121, 153, 185, 217, 249, 281, 313, 345, 377, 409, 441, 473, 505,
    26, 58, 90, 122, 154, 186, 218, 250, 282, 314, 346, 378, 410, 442, 474, 506, 27, 59, 91, 123, 155, 187, 219, 251,
    283, 315, 347, 379, 411, 443, 475, 507, 28, 60, 92, 124, 156, 188, 220, 252, 284, 316, 348, 380, 412, 444, 476, 508,
    29, 61, 93, 125, 157, 189, 221, 253, 285, 317, 349, 381, 413, 445, 477, 509, 30, 62, 94, 126, 158, 190, 222, 254,
    286, 318, 350, 382, 414, 446, 478, 510, 31, 63, 95, 127, 159, 191, 223, 255, 287, 319, 351, 383, 415, 447, 479, 511};
constexpr int kNSched = 576;
constexpr int kEnd = 0xffff;
struct Unit { int isA, b, h; };
DEVINL Unit decode_unit(int code) {
  Unit u;
  u.isA = code >> 9;
  u.b = (code >> 5) & 15;
  u.h = code & 31;
  return u;
}
DEVINL void wait_q(const Unit& u, unsigned ep1) {
  if (u.isA) wait_flag(&g_flags[(kFlagQA + u.h * 4 + (u.b >> 2)) * kFlagStride], ep1 * 4);
  else wait_flag(&g_flags[(kFlagQB + u.h * 4 + (u.b >> 2)) * kFlagStride], ep1);
}
__constant__ unsigned char c_qgroup[16] = {8, 9, 10, 11, 24, 12, 13, 25, 26, 14, 15, 27, 28, 29, 30, 31};

template <bool ACK>
DEVINL void store_row_bf16(uint32_t (&w)[16], __nv_bfloat16* row, int lane, uint32_t* ack) {
  const bool b0 = lane & 1, b1 = lane & 2;
#pragma unroll
  for (int m = 0; m < 4; m++) {
    uint32_t a0 = w[4 * m], a1 = w[4 * m + 1], a2 = w[4 * m + 2], a3 = w[4 * m + 3], t;
    t = __shfl_xor_sync(0xffffffffu, b0 ? a0 : a1, 1); if (b0) a0 = t; else a1 = t;
    t = __shfl_xor_sync(0xffffffffu, b0 ? a2 : a3, 1); if (b0) a2 = t; else a3 = t;
    t = __shfl_xor_sync(0xffffffffu, b1 ? a0 : a2, 2); if (b1) a0 = t; else a2 = t;
    t = __shfl_xor_sync(0xffffffffu, b1 ? a1 : a3, 2); if (b1) a1 = t; else a3 = t;
    __nv_bfloat16* p = row + (4 * m + (lane & 3)) * 8;
    asm volatile("st.global.v4.b32 [%0], {%1, %2, %3, %4};" ::"l"(p), "r"(a0), "r"(a1), "r"(a2), "r"(a3) : "memory");
    if (ACK) asm volatile("ld.relaxed.gpu.global.u32 %0, [%1];" : "=r"(ack[m]) : "l"(p) : "memory");
  }
}
DEVINL void store_half_row(uint32_t (&w)[8], __nv_bfloat16* row, int lane) {
  const bool b0 = lane & 1, b1 = lane & 2;
#pragma unroll
  for (int m = 0; m < 2; m++) {
    uint32_t a0 = w[4 * m], a1 = w[4 * m + 1], a2 = w[4 * m + 2], a3 = w[4 * m + 3], t;
    t = __shfl_xor_sync(0xffffffffu, b0 ? a0 : a1, 1); if (b0) a0 = t; else a1 = t;
    t = __shfl_xor_sync(0xffffffffu, b0 ? a2 : a3, 1); if (b0) a2 = t; else a3 = t;
    t = __shfl_xor_sync(0xffffffffu, b1 ? a0 : a2, 2); if (b1) a0 = t; else a2 = t;
    t = __shfl_xor_sync(0xffffffffu, b1 ? a1 : a3, 2); if (b1) a1 = t; else a3 = t;
    *reinterpret_cast<uint4*>(row + (4 * m + (lane & 3)) * 8) = make_uint4(a0, a1, a2, a3);
  }
}
template <bool ACK>
DEVINL void store_tile(const float (&o)[64], float i0, float i1, __nv_bfloat16* dst, int pitch, int lane, uint32_t (&ack)[8]) {
  uint32_t w[16];
#pragma unroll
  for (int n = 0; n < 16; n++) w[n] = pack_bf16(o[4 * n] * i0, o[4 * n + 1] * i0);
  store_row_bf16<ACK>(w, dst, lane, ack);
#pragma unroll
  for (int n = 0; n < 16; n++) w[n] = pack_bf16(o[4 * n + 2] * i1, o[4 * n + 3] * i1);
  store_row_bf16<ACK>(w, dst + 8 * pitch, lane, ack + 4);
}

__global__ void __launch_bounds__(512, 1) fused_kernel(const __grid_constant__ Maps maps, __nv_bfloat16* __restrict__ out,
                                                       const __nv_bfloat16* __restrict__ kA, const __nv_bfloat16* __restrict__ vA,
                                                       const __nv_bfloat16* __restrict__ kB, const __nv_bfloat16* __restrict__ vB,
                                                       const __nv_bfloat16* __restrict__ woA, const __nv_bfloat16* __restrict__ woB) {
  if (threadIdx.x == 0) TRACE(3, 30);
  extern __shared__ uint8_t smem_raw[];
  const uint32_t sraw = smem_u32(smem_raw);
  const uint32_t sbase = (sraw + 1023u) & ~1023u;
  uint8_t* sgen = smem_raw + (sbase - sraw);
  volatile uint32_t* s_misc = reinterpret_cast<volatile uint32_t*>(sgen + kSmemMisc);
  volatile uint32_t* s_order = reinterpret_cast<volatile uint32_t*>(sgen + kSmemStats);

  const int warp_idx = __shfl_sync(0xffffffffu, threadIdx.x >> 5, 0);
  const int lane = threadIdx.x & 31;
  const int wg = warp_idx >> 2;
  const int cta = blockIdx.x;
  constexpr int nattn = kNAttn;
  const bool is_attn = cta < nattn;
  const int oproj = cta - ((int)gridDim.x - kNOproj);
  const int oX = oproj >= 16, otile = oX ? (oproj - 16) >> 1 : oproj, og = otile >> 2, oi = otile & 3;
  const int onst = oX ? 32 : 64;
  const bool has_q = cta < 128;

  Ctx c;
  c.sbase = sbase;
  c.warp = warp_idx & 3;
  c.lane = lane;
  c.ft = -1;

  if (threadIdx.x < kMaxSeq) {
    mbar_init(bar_addr(c, kBarFull + threadIdx.x), (!is_attn && threadIdx.x < 64) ? 65 : 1);
    mbar_init(bar_addr(c, kBarEmpty + threadIdx.x), 12);
  } else if (threadIdx.x < kMaxSeq + kMaxUnits) {
    const int k = threadIdx.x - kMaxSeq;
    mbar_init(bar_addr(c, kBarSig + k), 12);
    mbar_init(bar_addr(c, kBarGo + k), 1);
    mbar_init(bar_addr(c, kBarUnit + k + 1), 1);
  } else if (threadIdx.x == kMaxSeq + kMaxUnits) {
    mbar_init(bar_addr(c, kBarEpoch), 1);
    mbar_init(bar_addr(c, kBarP1Done), 12);
    mbar_init(bar_addr(c, kBarRecv), 12);
    for (int s = 0; s < 3; s++) mbar_init(bar_addr(c, kBarQStored + s), 12);
    mbar_init(bar_addr(c, kBarP1bDone), 12);
    for (int s = 0; s < 3; s++) mbar_init(bar_addr(c, kBarQ0 + s), 1);
    s_misc[1] = cta < 64 ? (((cta & 3) * 4) << 5 | (cta >> 2)) : (cta < nattn ? c_sched[cta - 64] : kEnd);
  }
  asm volatile("fence.mbarrier_init.release.cluster;" ::: "memory");
  __syncthreads();
  asm volatile("barrier.cluster.arrive.release.aligned;" ::: "memory");
  if (threadIdx.x == 0) TRACE(3, 31);

  const int qX = cta < 64, qh = (cta & 63) >> 2, qg = cta & 3;
  const int n1b = oproj >= 16 ? 2 : 0;

  if (wg == 3) {
    asm volatile("setmaxnreg.dec.sync.aligned.u32 32;");
    auto kv_row = [&](const Unit& u, int i) { return (u.b * (u.isA ? 8 : 32) + u.h) * 512 + (i >> 1) * 64; };
    auto issue_kv = [&](const Unit& u, int i, int n, uint64_t pol) {
      const CUtensorMap* map = u.isA ? ((i & 1) ? &maps.vA : &maps.kA) : ((i & 1) ? &maps.vB : &maps.kB);
      mbar_expect_tx(bar_addr(c, kBarFull + n), kSlot);
      tma_3d_hint(sbase + (n % kRing) * kSlot, map, bar_addr(c, kBarFull + n), 0, kv_row(u, i), 0, pol);
    };
    auto o_loader = [&](int w) {
      const int X = oX, g = og;
      const int tt = w * 32 + lane, r8 = tt >> 3, ch = tt & 7;
      const uint8_t* src0 = reinterpret_cast<const uint8_t*>(g_Q) + (size_t)((X * 16 + g * 4) * 32) * 12288 + r8 * 256 + ch * 16;
      const uint32_t dst0 = sbase + r8 * 128 + ((ch ^ r8) << 4);
      mbar_wait(bar_addr(c, kBarP1bDone), 0);
      int head0 = 0;
#pragma unroll 1
      for (int n = 0; n < onst; n++) {
        const int sub = X ? n & 1 : n & 7;
        if (sub == 0) {
          const int q = X ? n >> 1 : n >> 3;
          mbar_wait(bar_addr(c, kBarFull + 96 + q), 0);
          head0 = s_order[q] * (X ? 1 : 4);
        }
        if (n >= kNO) mbar_wait(bar_addr(c, kBarEmpty + n - kNO), 0);
        if (w == 0 && lane == 0) OTRACE1(2, n);
        const uint8_t* src = src0 + (size_t)(head0 + (sub >> 1)) * 12288 + (sub & 1) * 128;
        const uint32_t dst = dst0 + (n % kNO) * kOStage;
#pragma unroll
        for (int j = 0; j < 24; j++)
          asm volatile("cp.async.cg.shared.global [%0], [%1], 16;" ::"r"(dst + j * 1024),
                       "l"(src + (size_t)(j / 6) * (32 * 12288) + (j % 6) * 2048) : "memory");
        asm volatile("cp.async.mbarrier.arrive.noinc.shared::cta.b64 [%0];" ::"r"(bar_addr(c, kBarFull + n)) : "memory");
      }
      asm volatile("cp.async.wait_all;" ::: "memory");
    };
    if (warp_idx == 12) {
      if (lane == 0 && is_attn) {
        uint64_t pol;
        asm volatile("createpolicy.fractional.L2::evict_first.b64 %0, 1.0;" : "=l"(pol));
        mbar_wait(bar_addr(c, kBarEpoch), 0);
        const unsigned ep1 = s_misc[0];
        mbar_wait(bar_addr(c, kBarP1Done), 0);
        int n = 0;
#pragma unroll 1
        for (int k = 0; k <= kMaxUnits; k++) {
          if (k > 0) mbar_wait(bar_addr(c, kBarUnit + k), 0);
          const int s = s_misc[1 + k];
          if (s == kEnd) break;
          mbar_arrive(bar_addr(c, kBarGo + k), 1);
          const Unit u = decode_unit(s);
          const int nq = u.isA ? 3 : 1;
          if (k < 20) TRACE(3, k);
          if (k == 0) {
            n = kPre;
#pragma unroll 1
            for (; n < kRing; n++) issue_kv(u, n, n, pol);
            if (cta >= 64) {
              wait_q(u, ep1);
              fence_proxy_async_global();
            }
          } else {
            fence_proxy_async_global();
          }
#pragma unroll 1
          for (int w = 0; w < ((k == 0 && cta < 64) ? 0 : nq); w++) {
            const int grp0 = u.isA ? (u.b * 32 + u.h * 4) * 3 + 4 * w : ((16 + u.b) * 32 + u.h) * 3;
            const uint32_t bytes = u.isA ? 16384u : 12288u;
            uint32_t fb, dst;
            if (k == 0) {
              fb = bar_addr(c, kBarQ0 + w);
              dst = sbase + kMergeOff + w * kSlot;
            } else {
              mbar_wait(bar_addr(c, kBarEmpty + n - kRing), 0);
              fb = bar_addr(c, kBarFull + n);
              dst = sbase + (n % kRing) * kSlot;
              n++;
            }
            mbar_expect_tx(fb, bytes);
            bulk_1d(dst, g_Q + (size_t)grp0 * 256, bytes, fb);
          }
#pragma unroll 1
          for (int i = k == 0 ? kRing : 0; i < 16; i++, n++) {
            mbar_wait(bar_addr(c, kBarEmpty + n - kRing), 0);
            issue_kv(u, i, n, pol);
          }
        }
        TRACE(3, 20);
      } else if (oproj >= 0) {
        const int X = oX, g = og;
        mbar_wait(bar_addr(c, kBarEpoch), 0);
        const unsigned target = s_misc[0] * 4;
        const unsigned* fp = &g_flags[(X == 0 ? kFlagOA + g * 8 + min(lane, 7)
                                              : kFlagOB + g * 32 + 2 * min(lane, 15) + (oproj & 1)) * kFlagStride];
        unsigned pending = X ? 0xffffu : 0xffu;
        int q = 0;
#pragma unroll 1
        for (int it = 0; pending != 0 && it < (1 << 22); it++) {
          const bool rdy = (int)(ld_acquire(fp) - target) >= 0;
          unsigned ready = __ballot_sync(0xffffffffu, rdy) & pending;
          pending &= ~ready;
          if (lane == 0) {
            while (ready) {
              const int st = __ffs(ready) - 1;
              ready &= ready - 1;
              s_order[q] = X ? 2 * st + (oproj & 1) : st;
              mbar_arrive(bar_addr(c, kBarFull + 96 + q), 1);
              if (X == 0 || (q & 1) == 0) TRACE(4, X ? q >> 1 : q);
              q++;
            }
          }
          q = __shfl_sync(0xffffffffu, q, 0);
        }
      }
    } else if (warp_idx == 13) {
      if (lane == 0) {
        uint64_t pol;
        asm volatile("createpolicy.fractional.L2::evict_first.b64 %0, 1.0;" : "=l"(pol));
        const Unit u0 = decode_unit(s_misc[1]);
        int kvn = 0;
        if (has_q) {
#pragma unroll 1
          for (int k = 0; k < 8; k++) {
            const uint32_t st = sbase + kQOff + (k % 3) * kQ1Stage;
            const uint32_t fb = bar_addr(c, kBarFull + kBar1a + k);
            if (k >= 3) mbar_wait(bar_addr(c, kBarEmpty + kBar1a + k - 3), 0);
            mbar_expect_tx(fb, kQ1Stage);
            tma_2d(st, qX ? &maps.xB : &maps.xA, fb, k * 64, qg * 192);
            tma_3d(st + 24576, qX ? &maps.wqB2 : &maps.wqA2, fb, 0, k * 64, qh * 2);
            if (is_attn && k >= 2 && kvn < kPre) { issue_kv(u0, kvn, kvn, pol); kvn++; }
          }
        }
        if (is_attn) {
          while (kvn < kPre) { issue_kv(u0, kvn, kvn, pol); kvn++; }
          mbar_wait(bar_addr(c, kBarEpoch), 0);
          const unsigned ep1 = s_misc[0];
#pragma unroll 1
          for (int k = 1; k <= kMaxUnits; k++) {
            mbar_wait(bar_addr(c, kBarGo + k - 1), 0);
            unsigned s = kEnd;
            if (k < kMaxUnits) {
              const unsigned pos = (nattn - 64) + atomicAdd(&g_next, 1u);
              if (pos < kNSched) s = c_sched[pos];
            }
            if (s != kEnd) wait_q(decode_unit(s), ep1);
            s_misc[1 + k] = s;
            mbar_arrive(bar_addr(c, kBarUnit + k), 1);
            if (s == kEnd) break;
          }
          if (atomicAdd(&g_sched_done, 1u) == nattn - 1) {
            g_next = 0;
            g_sched_done = 0;
          }
        } else if (oproj >= 0) {
          const int X = oX, i = oi;
          if (has_q) mbar_wait(bar_addr(c, kBarP1Done), 0);
#pragma unroll 1
          for (int n = 0; n < 8 * n1b; n++) {
            const int q = oproj - 16 + 32 * (n >> 3), k = n & 7;
            const int grp = c_qgroup[q >> 2], g = q & 3, X1 = grp >> 4, P = grp & 15;
            const uint32_t st = sbase + (n % 3) * kQStage;
            const uint32_t fb = bar_addr(c, kBarFull + kBar1b + n);
            if (n >= 3) mbar_wait(bar_addr(c, kBarEmpty + kBar1b + n - 3), 0);
            mbar_expect_tx(fb, kQStage);
            tma_2d(st, X1 ? &maps.xB : &maps.xA, fb, k * 64, g * 192);
            tma_3d(st + 24576, X1 ? &maps.wqB : &maps.wqA, fb, 0, k * 64, P * 4);
          }
          mbar_wait(bar_addr(c, kBarP1bDone), 0);
          int krow = 0;
#pragma unroll 1
          for (int n = 0; n < onst; n++) {
            const uint32_t fb = bar_addr(c, kBarFull + n);
            const int sub = X ? n & 1 : n & 7;
            if (sub == 0) {
              const int q = X ? n >> 1 : n >> 3;
              mbar_wait(bar_addr(c, kBarFull + 96 + q), 0);
              krow = s_order[q] * (X ? 128 : 512);
            }
            if (n >= kNO) mbar_wait(bar_addr(c, kBarEmpty + n - kNO), 0);
            OTRACE1(1, n);
            mbar_expect_tx(fb, 16384);
            tma_3d(sbase + (n % kNO) * kOStage + 24576, X ? &maps.woB : &maps.woA, fb, 0, krow + sub * 64, i * 2);
          }
        }
      }
    } else if (warp_idx == 14) {
      if (lane == 0) {
        if (has_q) {
          mbar_wait(bar_addr(c, kBarQStored), 0);
          asm volatile("fence.acq_rel.gpu;" ::: "memory");
          const int f = qX ? kFlagQB + qh * 4 + qg : kFlagQA + (qh >> 2) * 4 + qg;
          asm volatile("red.relaxed.gpu.global.add.u32 [%0], %1;" ::"l"(&g_flags[f * kFlagStride]), "r"(1u) : "memory");
          TRACE(4, 31);
        }
#pragma unroll 1
        for (int r = 0; r < n1b; r++) {
          const int q = oproj - 16 + 32 * r;
          const int grp = c_qgroup[q >> 2], g = q & 3, P = grp & 15;
          mbar_wait(bar_addr(c, kBarQStored + 1 + r), 0);
          asm volatile("fence.acq_rel.gpu;" ::: "memory");
          if (grp >> 4) {
            asm volatile("red.relaxed.gpu.global.add.u32 [%0], %1;" ::"l"(&g_flags[(kFlagQB + 2 * P * 4 + g) * kFlagStride]), "r"(1u) : "memory");
            asm volatile("red.relaxed.gpu.global.add.u32 [%0], %1;" ::"l"(&g_flags[(kFlagQB + (2 * P + 1) * 4 + g) * kFlagStride]), "r"(1u) : "memory");
          } else {
            asm volatile("red.relaxed.gpu.global.add.u32 [%0], %1;" ::"l"(&g_flags[(kFlagQA + (P >> 1) * 4 + g) * kFlagStride]), "r"(2u) : "memory");
          }
          TRACE(4, 29 + r);
        }
      }
      __syncwarp();
      if (oproj >= 0) {
        o_loader(0);
      } else if (lane == 0 && is_attn) {
#pragma unroll 1
        for (int k = 0; k <= kMaxUnits; k++) {
          if (k > 0) mbar_wait(bar_addr(c, kBarUnit + k), 0);
          const int s = s_misc[1 + k];
          if (s == kEnd) break;
          const Unit u = decode_unit(s);
          const int f = u.isA ? kFlagOA + (u.b >> 2) * 8 + u.h : kFlagOB + (u.b >> 2) * 32 + u.h;
          mbar_wait(bar_addr(c, kBarSig + k), 0);
          asm volatile("fence.acq_rel.gpu;" ::: "memory");
          asm volatile("red.relaxed.gpu.global.add.u32 [%0], %1;" ::"l"(&g_flags[f * kFlagStride]), "r"(1u) : "memory");
          if (k < 12) TRACE(4, 16 + k);
        }
      }
    } else {
      if (lane == 0) {
        unsigned e;
        asm volatile("ld.relaxed.gpu.global.u32 %0, [%1];" : "=r"(e) : "l"(&g_epoch) : "memory");
        s_misc[0] = e + 1;
        mbar_arrive(bar_addr(c, kBarEpoch), 1);
        unsigned old = atomicAdd(&g_started, 1u);
        if (old == gridDim.x - 1) {
          g_started = 0;
          __threadfence();
          asm volatile("st.relaxed.gpu.global.u32 [%0], %1;" ::"l"(&g_epoch), "r"(e + 1) : "memory");
        }
      }
      __syncwarp();
      if (is_attn && kWarm > 0) {
        const Unit u0 = decode_unit(s_misc[1]);
        unsigned sink = 0;
#pragma unroll 1
        for (int i = kPre; i < kPre + kWarm; i++) {
          __nanosleep(800);
          const __nv_bfloat16* src = u0.isA ? ((i & 1) ? vA : kA) : ((i & 1) ? vB : kB);
          src += (size_t)kv_row(u0, i) * 128 + lane * 64;
#pragma unroll
          for (int j = 0; j < 4; j++) {
            unsigned v;
            asm volatile("ld.global.L2::128B.b32 %0, [%1];" : "=r"(v) : "l"(src + j * 2048));
            sink ^= v;
          }
        }
        if (sink == 0x9e3779b9u) s_misc[24] = sink;
      } else if (oproj >= 0) {
        mbar_wait_warp(bar_addr(c, kBarP1Done), has_q ? 0 : 1);
        unsigned sink = 0;
#pragma unroll 1
        for (int it = 0; it < 6; it++) {
          unsigned v[8];
#pragma unroll
          for (int j = 0; j < 4; j++) {
            const int l = min((it * 4 + j) * 1536 + oproj * 32 + lane, 32767);
            asm volatile("ld.global.L2::128B.b32 %0, [%1];" : "=r"(v[2 * j]) : "l"(woA + (size_t)l * 64));
            asm volatile("ld.global.L2::128B.b32 %0, [%1];" : "=r"(v[2 * j + 1]) : "l"(woB + (size_t)l * 64));
          }
          sink ^= v[0] ^ v[1] ^ v[2] ^ v[3] ^ v[4] ^ v[5] ^ v[6] ^ v[7];
        }
        if (sink == 0x9e3779b9u) s_misc[24] = sink;
        o_loader(1);
      }
    }
  } else {
    asm volatile("setmaxnreg.inc.sync.aligned.u32 160;");
    if (has_q) {
      float acc[64];
      CTRACE(0);
#pragma unroll 1
      for (int k = 0; k < 8; k++) {
        const uint32_t st = sbase + kQOff + (k % 3) * kQ1Stage;
        mbar_wait_warp(bar_addr(c, kBarFull + kBar1a + k), 0);
        const uint64_t da = make_desc(st + wg * 8192, 16, 1024);
        const uint64_t db = make_desc(st + 24576, 8192, 1024);
        fence_regs(acc);
        wgmma_fence();
#pragma unroll
        for (int j = 0; j < 4; j++) wgmma_ss_n128_tb(acc, da + j * 2, db + j * 128, (k | j) != 0);
        wgmma_commit();
        wgmma_wait<0>();
        if (lane == 0) mbar_arrive(bar_addr(c, kBarEmpty + kBar1a + k), 1);
      }
      fence_regs(acc);
      CTRACE(1);
      const int G = 4 * wg + c.warp;
      if (lane == 0) mbar_arrive(bar_addr(c, kBarP1Done), 1);
      if (cta < 64) {
        bar_sync(1, 384);
        if (G < 3) store_frag(reinterpret_cast<uint4*>(sgen + kMergeOff) + G * 256, acc, lane);
        bar_sync(2, 384);
      }
      store_frag(g_Q + (size_t)(((qX * 16 + qg * 4 + G / 3) * 32 + qh) * 3 + G % 3) * 256, acc, lane);
      __syncwarp();
      if (lane == 0) mbar_arrive(bar_addr(c, kBarQStored), 1);
      CTRACE(2);
    }
    if (oproj >= 0) {
      float acc[2][64];
#pragma unroll 1
      for (int r = 0; r < n1b; r++) {
#pragma unroll 1
        for (int k = 0; k < 8; k++) {
          const int n = r * 8 + k;
          const uint32_t st = sbase + (n % 3) * kQStage;
          mbar_wait_warp(bar_addr(c, kBarFull + kBar1b + n), 0);
          const uint64_t da = make_desc(st + wg * 8192, 16, 1024);
          const uint64_t db = make_desc(st + 24576, 8192, 1024);
          fence_regs(acc[0]);
          fence_regs(acc[1]);
          wgmma_fence();
#pragma unroll
          for (int j = 0; j < 4; j++) {
            wgmma_ss_n128_tb(acc[0], da + j * 2, db + j * 128, (k | j) != 0);
            wgmma_ss_n128_tb(acc[1], da + j * 2, db + 1024 + j * 128, (k | j) != 0);
          }
          wgmma_commit();
          wgmma_wait<0>();
          if (lane == 0) mbar_arrive(bar_addr(c, kBarEmpty + kBar1b + n), 1);
        }
        fence_regs(acc[0]);
        fence_regs(acc[1]);
        const int q = oproj - 16 + 32 * r;
        const int grp = c_qgroup[q >> 2], g = q & 3, X1 = grp >> 4, P = grp & 15;
        const int G = 4 * wg + c.warp;
        uint4* dst = g_Q + (size_t)(((X1 * 16 + g * 4 + G / 3) * 32 + 2 * P) * 3 + G % 3) * 256;
        store_frag(dst, acc[0], lane);
        store_frag(dst + 3 * 256, acc[1], lane);
        __syncwarp();
        if (lane == 0) mbar_arrive(bar_addr(c, kBarQStored + 1 + r), 1);
        CTRACE(16 + r);
      }
      if (lane == 0) mbar_arrive(bar_addr(c, kBarP1bDone), 1);
    }

    if (is_attn) {
      if (FK_TOK && wg == 2) bar_arrive(4, 256);
      int base = 0;
      float2* stats = reinterpret_cast<float2*>(sgen + kSmemStats);
      uint32_t ack[8];
#pragma unroll 1
      for (int k = 0; k <= kMaxUnits; k++) {
        if (k > 0) mbar_wait_warp(bar_addr(c, kBarUnit + k), 0);
        const int s = __shfl_sync(0xffffffffu, (int)s_misc[1 + k], 0);
        if (s == kEnd) break;
        const bool isA = s >> 9;
        const int nq = k == 0 ? 0 : (isA ? 3 : 1);
        uint32_t qf[32];
        {
          const int w = isA ? wg : 0;
          const int n = base + w;
          if (k > 0 || cta >= 64) mbar_wait_warp(bar_addr(c, k == 0 ? kBarQ0 + w : kBarFull + n), 0);
          const uint4* q = reinterpret_cast<const uint4*>(sgen + (k == 0 ? kMergeOff + w * kSlot : (n % kRing) * kSlot)) +
                           (isA || c.warp < 3 ? c.warp : 2) * 256 + lane;
#pragma unroll
          for (int j = 0; j < 8; j++) {
            const uint4 v = q[j * 32];
            qf[4 * j] = v.x; qf[4 * j + 1] = v.y; qf[4 * j + 2] = v.z; qf[4 * j + 3] = v.w;
          }
        }
        float o[64];
        float m0, m1, l0, l1;
        if (k < 9) CTRACE(4 + 3 * k);
        c.ft = k == FK_FTK ? (cta * 3 + wg) * 64 : -1;
        attention(c, qf, base + nq, isA ? 0 : wg, isA ? 1 : 3, isA ? 8 : 3, wg, k > 0 ? kBarEmpty + base + (isA ? wg : 0) : -1,
                  isA ? 1u : 3u, isA ? 3u : 1u, o, m0, m1, l0, l1);
        if (k < 9) CTRACE(5 + 3 * k);
        int s2 = s;
        asm volatile("" : "+r"(s2));
        const Unit u = decode_unit(s2);
        if (isA) {
          const int G = 4 * wg + c.warp;
          store_tile<false>(o, rcp_approx(l0), rcp_approx(l1),
                     reinterpret_cast<__nv_bfloat16*>(g_Q) + (size_t)(u.b * 32 + u.h * 4 + G / 3) * 6144 + ((G % 3) * 16 + (lane >> 2)) * 128,
                     128, lane, ack);
          __syncwarp();
          if (lane == 0) mbar_arrive(bar_addr(c, kBarSig + k), 1);
        } else {
          const int r0 = c.warp * 16 + (lane >> 2);
          if (c.warp < 3 && (lane & 3) == 0) {
            stats[wg * 48 + r0] = make_float2(m0, l0);
            stats[wg * 48 + r0 + 8] = make_float2(m1, l1);
          }
          bar_sync(1, 384);
          const int fin = k % 3;
          if (c.warp < 3) {
            const float2 xa = stats[r0], xb = stats[48 + r0], xc = stats[96 + r0];
            const float2 ya = stats[r0 + 8], yb = stats[48 + r0 + 8], yc = stats[96 + r0 + 8];
            const float mx = fmaxf(xa.x, fmaxf(xb.x, xc.x)), my = fmaxf(ya.x, fmaxf(yb.x, yc.x));
            const float lx = xa.y * ex2((xa.x - mx) * kScale) + xb.y * ex2((xb.x - mx) * kScale) + xc.y * ex2((xc.x - mx) * kScale);
            const float ly = ya.y * ex2((ya.x - my) * kScale) + yb.y * ex2((yb.x - my) * kScale) + yc.y * ex2((yc.x - my) * kScale);
            const float f0 = ex2((m0 - mx) * kScale) * rcp_approx(lx), f1 = ex2((m1 - my) * kScale) * rcp_approx(ly);
#pragma unroll
            for (int n = 0; n < 16; n++) {
              o[4 * n] *= f0; o[4 * n + 1] *= f0;
              o[4 * n + 2] *= f1; o[4 * n + 3] *= f1;
            }
            if (wg != fin) {
              float4* dst = reinterpret_cast<float4*>(sgen + kMergeOff) + ((wg + 3 - fin) % 3 - 1) * (16 * 96) + c.warp * 32 + lane;
#pragma unroll
              for (int n = 0; n < 16; n++) dst[n * 96] = make_float4(o[4 * n], o[4 * n + 1], o[4 * n + 2], o[4 * n + 3]);
            }
          }
          bar_sync(2, 384);
          if (wg == fin && c.warp < 3) {
            const float4* src = reinterpret_cast<const float4*>(sgen + kMergeOff) + c.warp * 32 + lane;
#pragma unroll
            for (int n = 0; n < 16; n++) {
              const float4 x = src[n * 96], y = src[16 * 96 + n * 96];
              o[4 * n] += x.x + y.x; o[4 * n + 1] += x.y + y.y;
              o[4 * n + 2] += x.z + y.z; o[4 * n + 3] += x.w + y.w;
            }
            store_tile<false>(o, 1.f, 1.f, reinterpret_cast<__nv_bfloat16*>(g_Q) + (size_t)((16 + u.b) * 32 + u.h) * 6144 + r0 * 128, 128, lane, ack);
            __syncwarp();
            if (lane == 0) mbar_arrive(bar_addr(c, kBarSig + k), 4);
          }
        }
        if (k < 9) CTRACE(6 + 3 * k);
        base += 16 + nq;
      }
    } else if (oproj >= 0) {
      float acc[64];
#pragma unroll 1
      for (int n = 0; n < onst; n++) {
        const int slot = n % kNO;
        const uint32_t st = sbase + slot * kOStage;
        mbar_wait_warp(bar_addr(c, kBarFull + n), 0);
        OTRACE(0, n);
        asm volatile("fence.proxy.async.shared::cta;" ::: "memory");
        const uint64_t da = make_desc(st + wg * 8192, 16, 1024);
        const uint64_t db = make_desc(st + 24576, 8192, 1024);
        fence_regs(acc);
        wgmma_fence();
#pragma unroll
        for (int j = 0; j < 4; j++) wgmma_ss_n128_tb(acc, da + j * 2, db + j * 128, (n | j) != 0);
        wgmma_commit();
        wgmma_wait<0>();
        if (lane == 0) mbar_arrive(bar_addr(c, kBarEmpty + n), 1);
        if ((n & 7) == 7) CTRACE(4 + (n >> 3));
      }
      fence_regs(acc);
      const int tid = threadIdx.x;
      __nv_bfloat16* orow = out + (size_t)(og * 192 + wg * 64 + c.warp * 16 + (lane >> 2)) * 1024 + oX * 512 + oi * 128;
      if (oX) {
        const int r = cta & 1;
        asm volatile("barrier.cluster.wait.acquire.aligned;" ::: "memory");
        const uint32_t dst = mapa(sbase + kRecvOff, r ^ 1) + tid * 16;
        if (r == 0) {
#pragma unroll
          for (int n = 0; n < 8; n++)
            asm volatile("st.shared::cluster.v4.f32 [%0], {%1, %2, %3, %4};" ::"r"(dst + n * 6144), "f"(acc[32 + 4 * n]),
                         "f"(acc[33 + 4 * n]), "f"(acc[34 + 4 * n]), "f"(acc[35 + 4 * n]) : "memory");
        } else {
#pragma unroll
          for (int n = 0; n < 8; n++)
            asm volatile("st.shared::cluster.v4.f32 [%0], {%1, %2, %3, %4};" ::"r"(dst + n * 6144), "f"(acc[4 * n]),
                         "f"(acc[4 * n + 1]), "f"(acc[4 * n + 2]), "f"(acc[4 * n + 3]) : "memory");
        }
        __syncwarp();
        if (lane == 0) mbar_arrive_remote(mapa(bar_addr(c, kBarRecv), r ^ 1));
        asm volatile(
            "{\n.reg .pred p;\n.reg .u32 n;\nmov.u32 n, 0;\n"
            "RW_LOOP:\n"
            "mbarrier.try_wait.parity.acquire.cluster.shared::cta.b64 p, [%0], 0;\n"
            "@p bra RW_DONE;\n"
            "add.u32 n, n, 1;\nsetp.lt.u32 p, n, 0x100000;\n@p bra RW_LOOP;\n"
            "RW_DONE:\n}\n" ::"r"(bar_addr(c, kBarRecv)) : "memory");
        __syncwarp();
        const float4* src = reinterpret_cast<const float4*>(sgen + kRecvOff) + tid;
        uint32_t w0[8], w1[8];
#pragma unroll
        for (int n = 0; n < 8; n++) {
          const float4 x = src[n * 384];
          const float a0 = (r ? acc[32 + 4 * n] : acc[4 * n]) + x.x, a1 = (r ? acc[33 + 4 * n] : acc[4 * n + 1]) + x.y;
          const float a2 = (r ? acc[34 + 4 * n] : acc[4 * n + 2]) + x.z, a3 = (r ? acc[35 + 4 * n] : acc[4 * n + 3]) + x.w;
          w0[n] = pack_bf16(a0, a1);
          w1[n] = pack_bf16(a2, a3);
        }
        store_half_row(w0, orow + r * 64, lane);
        store_half_row(w1, orow + 8 * 1024 + r * 64, lane);
      } else {
        uint32_t dummy_ack[8];
        store_tile<false>(acc, 1.f, 1.f, orow, 1024, lane, dummy_ack);
      }
      CTRACE(13);
    }
  }
}

typedef CUresult (*EncodeFn)(CUtensorMap*, CUtensorMapDataType, cuuint32_t, void*, const cuuint64_t*,
                             const cuuint64_t*, const cuuint32_t*, const cuuint32_t*, CUtensorMapInterleave,
                             CUtensorMapSwizzle, CUtensorMapL2promotion, CUtensorMapFloatOOBfill);

static bool make_map_2d(EncodeFn enc, CUtensorMap* m, const void* ptr, uint64_t cols, uint64_t rows,
                        uint32_t box_rows) {
  cuuint64_t dims[2] = {cols, rows};
  cuuint64_t strides[1] = {cols * 2};
  cuuint32_t box[2] = {64, box_rows};
  cuuint32_t es[2] = {1, 1};
  return enc(m, CU_TENSOR_MAP_DATA_TYPE_BFLOAT16, 2, const_cast<void*>(ptr), dims, strides, box, es,
             CU_TENSOR_MAP_INTERLEAVE_NONE, CU_TENSOR_MAP_SWIZZLE_128B, CU_TENSOR_MAP_L2_PROMOTION_L2_256B,
             CU_TENSOR_MAP_FLOAT_OOB_FILL_NONE) == CUDA_SUCCESS;
}
static bool make_map_3d(EncodeFn enc, CUtensorMap* m, const void* ptr, uint64_t cols, uint64_t rows, uint32_t nblk) {
  cuuint64_t dims[3] = {64, rows, cols / 64};
  cuuint64_t strides[2] = {cols * 2, 128};
  cuuint32_t box[3] = {64, 64, nblk};
  cuuint32_t es[3] = {1, 1, 1};
  return enc(m, CU_TENSOR_MAP_DATA_TYPE_BFLOAT16, 3, const_cast<void*>(ptr), dims, strides, box, es,
             CU_TENSOR_MAP_INTERLEAVE_NONE, CU_TENSOR_MAP_SWIZZLE_128B, CU_TENSOR_MAP_L2_PROMOTION_L2_256B,
             CU_TENSOR_MAP_FLOAT_OOB_FILL_NONE) == CUDA_SUCCESS;
}

}

extern "C" void kernel_launch(void* const* d_in, const int* in_sizes, int n_in, void* d_out, int out_size) {
  using namespace fk;
  (void)in_sizes; (void)n_in; (void)out_size;
  static EncodeFn enc = nullptr;
  static void* o_ptr = nullptr;
  static int nsm = 0;
  if (!enc) {
    void* fn = nullptr;
    cudaDriverEntryPointQueryResult qres;
    cudaGetDriverEntryPoint("cuTensorMapEncodeTiled", &fn, cudaEnableDefault, &qres);
    enc = (EncodeFn)fn;
    cudaGetSymbolAddress(&o_ptr, g_Q);
    cudaFuncSetAttribute(fused_kernel, cudaFuncAttributeMaxDynamicSharedMemorySize, kSmemTotal);
    int dev = 0;
    cudaGetDevice(&dev);
    cudaDeviceGetAttribute(&nsm, cudaDevAttrMultiProcessorCount, dev);
    if (nsm > 132) nsm = 132;
  }
  Maps maps;
  bool ok = true;
  ok &= make_map_2d(enc, &maps.xA, d_in[0], 512, 768, 192);
  ok &= make_map_3d(enc, &maps.kA, d_in[1], 128, 16 * 8 * 512, 2);
  ok &= make_map_3d(enc, &maps.vA, d_in[2], 128, 16 * 8 * 512, 2);
  ok &= make_map_3d(enc, &maps.wqA, d_in[3], 4096, 512, 4);
  ok &= make_map_3d(enc, &maps.woA, d_in[4], 512, 4096, 2);
  ok &= make_map_2d(enc, &maps.xB, d_in[5], 512, 768, 192);
  ok &= make_map_3d(enc, &maps.kB, d_in[6], 128, 16 * 32 * 512, 2);
  ok &= make_map_3d(enc, &maps.vB, d_in[7], 128, 16 * 32 * 512, 2);
  ok &= make_map_3d(enc, &maps.wqB, d_in[8], 4096, 512, 4);
  ok &= make_map_3d(enc, &maps.woB, d_in[9], 512, 4096, 2);
  ok &= make_map_3d(enc, &maps.wqA2, d_in[3], 4096, 512, 2);
  ok &= make_map_3d(enc, &maps.wqB2, d_in[8], 4096, 512, 2);
  if (!ok) return;
  cudaLaunchConfig_t cfg = {};
  cfg.gridDim = dim3(nsm);
  cfg.blockDim = dim3(512);
  cfg.dynamicSmemBytes = kSmemTotal;
  cfg.stream = cudaStreamPerThread;
  cudaLaunchAttribute attr[1];
  attr[0].id = cudaLaunchAttributeClusterDimension;
  attr[0].val.clusterDim.x = 2; attr[0].val.clusterDim.y = 1; attr[0].val.clusterDim.z = 1;
  cfg.attrs = attr;
  cfg.numAttrs = 1;
  cudaLaunchKernelEx(&cfg, fused_kernel, maps, (__nv_bfloat16*)d_out, (const __nv_bfloat16*)d_in[1],
                     (const __nv_bfloat16*)d_in[2], (const __nv_bfloat16*)d_in[6], (const __nv_bfloat16*)d_in[7],
                     (const __nv_bfloat16*)d_in[4], (const __nv_bfloat16*)d_in[9]);
}
```

```cpp
#include <cuda_runtime.h>
#include <cuda_bf16.h>
#include <cuda.h>
#include <stdint.h>

#define DEVINL __device__ __forceinline__

namespace fk {

constexpr int kNOproj = 48;
constexpr int kNAttn = 84;
constexpr int kSlot = 16384;
constexpr int kRing = 10;
constexpr int kPre = 6;
constexpr int kEarlyKV = 2;
constexpr int kQ1Stage = 40960;
constexpr int kQOff = 6 * kSlot;
constexpr int kQStage = 57344;
constexpr int kBar1 = 200;
constexpr int kOStage = 40960;
constexpr int kNOA = 5, kNOB = 4;
constexpr int kRecvOff = kNOB * kOStage;
constexpr int kMergeOff = 10 * kSlot;
constexpr int kSmemBar = 216 * 1024;
constexpr int kMaxUnits = 10;
constexpr int kMaxSeq = 228;

constexpr int kBarFull = 0;
constexpr int kBarEmpty = kMaxSeq;
constexpr int kBarEpoch = 2 * kMaxSeq;
constexpr int kBarP1Done = kBarEpoch + 1;
constexpr int kBarQ0 = kBarP1Done + 1;
constexpr int kBarQStored = kBarQ0 + 3;
constexpr int kBarRecv = kBarQStored + 2;
constexpr int kBarGo = kBarRecv + 2;
constexpr int kBarUnit = kBarGo + kMaxUnits;
constexpr int kBarSig = kBarUnit + kMaxUnits + 1;
constexpr int kNumBars = kBarSig + kMaxUnits;
constexpr int kSmemMisc = kSmemBar + kNumBars * 8;
constexpr int kSmemStats = kSmemMisc + 128;
constexpr int kSmemTotal = kSmemStats + 3 * 48 * 8 + 1024;

struct Maps {
  CUtensorMap kA, vA, kB, vB, xA, xB, wqA, wqB, woA, woB, wqB2;
};

__device__ uint4 g_Q[2 * 16 * 32 * 3 * 256];
constexpr int kFlagStride = 32;
constexpr int kFlagQB = 0;
constexpr int kFlagQA = 128;
constexpr int kFlagOA = 160;
constexpr int kFlagOB = 192;
constexpr int kNumFlags = 320;
__device__ unsigned g_flags[kNumFlags * kFlagStride];
__device__ unsigned g_epoch;
__device__ unsigned g_started;
__device__ unsigned g_next;
__device__ unsigned g_sched_done;

DEVINL uint32_t smem_u32(const void* p) { return (uint32_t)__cvta_generic_to_shared(p); }
DEVINL void mbar_init(uint32_t bar, uint32_t cnt) {
  asm volatile("mbarrier.init.shared::cta.b64 [%0], %1;" ::"r"(bar), "r"(cnt) : "memory");
}
DEVINL void mbar_expect_tx(uint32_t bar, uint32_t bytes) {
  asm volatile("mbarrier.arrive.expect_tx.shared::cta.b64 _, [%0], %1;" ::"r"(bar), "r"(bytes) : "memory");
}
DEVINL void mbar_arrive(uint32_t bar, uint32_t cnt) {
  asm volatile("mbarrier.arrive.shared::cta.b64 _, [%0], %1;" ::"r"(bar), "r"(cnt) : "memory");
}
DEVINL bool mbar_try(uint32_t bar, uint32_t parity) {
  uint32_t ok;
  asm volatile(
      "{\n.reg .pred p;\n"
      "mbarrier.try_wait.parity.shared::cta.b64 p, [%1], %2;\n"
      "selp.u32 %0, 1, 0, p;\n}\n"
      : "=r"(ok)
      : "r"(bar), "r"(parity)
      : "memory");
  return ok != 0;
}
DEVINL void mbar_wait(uint32_t bar, uint32_t parity) {
  asm volatile(
      "{\n.reg .pred p;\n.reg .u32 n;\n"
      "mov.u32 n, 0;\n"
      "WAIT_LOOP:\n"
      "mbarrier.try_wait.parity.shared::cta.b64 p, [%0], %1;\n"
      "@p bra WAIT_DONE;\n"
      "add.u32 n, n, 1;\n"
      "setp.lt.u32 p, n, 0x100000;\n"
      "@p bra WAIT_LOOP;\n"
      "WAIT_DONE:\n}\n"
      ::"r"(bar), "r"(parity)
      : "memory");
}
DEVINL void mbar_wait_warp(uint32_t bar, uint32_t parity) {
  asm volatile(
      "{\n.reg .pred p, q;\n.reg .u32 n;\n"
      "mov.u32 n, 0;\n"
      "WAIT_LOOP:\n"
      "mbarrier.try_wait.parity.shared::cta.b64 p, [%0], %1;\n"
      "vote.sync.all.pred q, p, 0xffffffff;\n"
      "@q bra WAIT_DONE;\n"
      "add.u32 n, n, 1;\n"
      "setp.lt.u32 p, n, 0x100000;\n"
      "@p bra WAIT_LOOP;\n"
      "WAIT_DONE:\n}\n"
      ::"r"(bar), "r"(parity)
      : "memory");
}
DEVINL void tma_3d(uint32_t dst, const CUtensorMap* map, uint32_t bar, int c0, int c1, int c2) {
  asm volatile(
      "cp.async.bulk.tensor.3d.shared::cluster.global.mbarrier::complete_tx::bytes [%0], [%1, {%3, %4, %5}], [%2];"
      ::"r"(dst), "l"(map), "r"(bar), "r"(c0), "r"(c1), "r"(c2)
      : "memory");
}
DEVINL void tma_3d_hint(uint32_t dst, const CUtensorMap* map, uint32_t bar, int c0, int c1, int c2, uint64_t pol) {
  asm volatile(
      "cp.async.bulk.tensor.3d.shared::cluster.global.mbarrier::complete_tx::bytes.L2::cache_hint [%0], [%1, {%3, "
      "%4, %5}], [%2], %6;"
      ::"r"(dst), "l"(map), "r"(bar), "r"(c0), "r"(c1), "r"(c2), "l"(pol)
      : "memory");
}
DEVINL void tma_2d(uint32_t dst, const CUtensorMap* map, uint32_t bar, int c0, int c1) {
  asm volatile(
      "cp.async.bulk.tensor.2d.shared::cluster.global.mbarrier::complete_tx::bytes [%0], [%1, {%3, %4}], [%2];"
      ::"r"(dst), "l"(map), "r"(bar), "r"(c0), "r"(c1)
      : "memory");
}
DEVINL uint32_t mapa(uint32_t addr, uint32_t rank) {
  uint32_t r;
  asm volatile("mapa.shared::cluster.u32 %0, %1, %2;" : "=r"(r) : "r"(addr), "r"(rank));
  return r;
}
DEVINL void mbar_arrive_remote(uint32_t cluster_addr) {
  asm volatile("mbarrier.arrive.release.cluster.shared::cluster.b64 _, [%0];" ::"r"(cluster_addr) : "memory");
}
DEVINL void bulk_1d(uint32_t dst, const void* src, uint32_t bytes, uint32_t bar) {
  asm volatile("cp.async.bulk.shared::cluster.global.mbarrier::complete_tx::bytes [%0], [%1], %2, [%3];"
               ::"r"(dst), "l"(src), "r"(bytes), "r"(bar)
               : "memory");
}
DEVINL unsigned ld_acquire(const unsigned* p) {
  unsigned v;
  asm volatile("ld.acquire.gpu.global.u32 %0, [%1];" : "=r"(v) : "l"(p) : "memory");
  return v;
}
DEVINL void wait_flag(const unsigned* p, unsigned target) {
  for (int n = 0; n < (1 << 22); n++) {
    if ((int)(ld_acquire(p) - target) >= 0) break;
  }
}
DEVINL void bar_sync(int id, int n) { asm volatile("bar.sync %0, %1;" ::"r"(id), "r"(n) : "memory"); }
DEVINL void bar_arrive(int id, int n) { asm volatile("bar.arrive %0, %1;" ::"r"(id), "r"(n) : "memory"); }
DEVINL void fence_proxy_async_global() { asm volatile("fence.proxy.async.global;" ::: "memory"); }

DEVINL void wgmma_fence() { asm volatile("wgmma.fence.sync.aligned;" ::: "memory"); }
DEVINL void wgmma_commit() { asm volatile("wgmma.commit_group.sync.aligned;" ::: "memory"); }
template <int N>
DEVINL void wgmma_wait() {
  asm volatile("wgmma.wait_group.sync.aligned %0;" ::"n"(N) : "memory");
}
template <int N>
DEVINL void fence_regs(float (&d)[N]) {
#pragma unroll
  for (int i = 0; i < N; i++) asm volatile("" : "+f"(d[i])::"memory");
}
template <int N>
DEVINL void fence_regs(uint32_t (&d)[N]) {
#pragma unroll
  for (int i = 0; i < N; i++) asm volatile("" : "+r"(d[i])::"memory");
}

DEVINL uint64_t make_desc(uint32_t addr, uint32_t lbo, uint32_t sbo) {
  return (uint64_t)((addr & 0x3FFFF) >> 4) | ((uint64_t)(lbo >> 4) << 16) | ((uint64_t)(sbo >> 4) << 32) |
         (1ull << 62);
}

#define F8(d, o) "+f"(d[o + 0]), "+f"(d[o + 1]), "+f"(d[o + 2]), "+f"(d[o + 3]), "+f"(d[o + 4]), "+f"(d[o + 5]), "+f"(d[o + 6]), "+f"(d[o + 7])
#define F32(d, o) F8(d, o), F8(d, o + 8), F8(d, o + 16), F8(d, o + 24)
#define R32 "%0, %1, %2, %3, %4, %5, %6, %7, %8, %9, %10, %11, %12, %13, %14, %15, %16, %17, %18, %19, %20, %21, %22, %23, %24, %25, %26, %27, %28, %29, %30, %31"
#define R64 R32 ", %32, %33, %34, %35, %36, %37, %38, %39, %40, %41, %42, %43, %44, %45, %46, %47, %48, %49, %50, %51, %52, %53, %54, %55, %56, %57, %58, %59, %60, %61, %62, %63"

DEVINL void wgmma_ss_n128_tb(float (&d)[64], uint64_t da, uint64_t db, int scale_d) {
  asm volatile(
      "{\n.reg .pred p;\nsetp.ne.b32 p, %66, 0;\n"
      "wgmma.mma_async.sync.aligned.m64n128k16.f32.bf16.bf16 {" R64 "}, %64, %65, p, 1, 1, 0, 1;\n}\n"
      : F32(d, 0), F32(d, 32)
      : "l"(da), "l"(db), "r"(scale_d));
}
DEVINL void wgmma_rs_n128_tb(float (&d)[64], uint32_t a0, uint32_t a1, uint32_t a2, uint32_t a3, uint64_t db,
                             int scale_d) {
  asm volatile(
      "{\n.reg .pred p;\nsetp.ne.b32 p, %69, 0;\n"
      "wgmma.mma_async.sync.aligned.m64n128k16.f32.bf16.bf16 {" R64 "}, {%64, %65, %66, %67}, %68, p, 1, 1, 1;\n}\n"
      : F32(d, 0), F32(d, 32)
      : "r"(a0), "r"(a1), "r"(a2), "r"(a3), "l"(db), "r"(scale_d));
}
DEVINL void wgmma_rs_n64(float (&d)[32], uint32_t a0, uint32_t a1, uint32_t a2, uint32_t a3, uint64_t db,
                         int scale_d) {
  asm volatile(
      "{\n.reg .pred p;\nsetp.ne.b32 p, %37, 0;\n"
      "wgmma.mma_async.sync.aligned.m64n64k16.f32.bf16.bf16 {" R32 "}, {%32, %33, %34, %35}, %36, p, 1, 1, 0;\n}\n"
      : F32(d, 0)
      : "r"(a0), "r"(a1), "r"(a2), "r"(a3), "l"(db), "r"(scale_d));
}

#define O8(d, o) "=f"(d[o + 0]), "=f"(d[o + 1]), "=f"(d[o + 2]), "=f"(d[o + 3]), "=f"(d[o + 4]), "=f"(d[o + 5]), "=f"(d[o + 6]), "=f"(d[o + 7])
#define O32(d, o) O8(d, o), O8(d, o + 8), O8(d, o + 16), O8(d, o + 24)
DEVINL void wgmma_rs_n64_init(float (&d)[32], uint32_t a0, uint32_t a1, uint32_t a2, uint32_t a3, uint64_t db) {
  asm volatile(
      "{\n.reg .pred p;\nsetp.ne.b32 p, %37, 0;\n"
      "wgmma.mma_async.sync.aligned.m64n64k16.f32.bf16.bf16 {" R32 "}, {%32, %33, %34, %35}, %36, p, 1, 1, 0;\n}\n"
      : O32(d, 0)
      : "r"(a0), "r"(a1), "r"(a2), "r"(a3), "l"(db), "r"(0));
}
DEVINL float rcp_approx(float x) {
  float y;
  asm("rcp.approx.ftz.f32 %0, %1;" : "=f"(y) : "f"(x));
  return y;
}

DEVINL uint32_t pack_bf16(float lo, float hi) {
  uint32_t r;
  asm("cvt.rn.bf16x2.f32 %0, %1, %2;" : "=r"(r) : "f"(hi), "f"(lo));
  return r;
}
DEVINL float ex2(float x) {
  float y;
  asm("ex2.approx.ftz.f32 %0, %1;" : "=f"(y) : "f"(x));
  return y;
}

struct Ctx {
  uint32_t sbase;
  int warp;
  int lane;
};
DEVINL uint32_t bar_addr(const Ctx& c, int idx) { return c.sbase + kSmemBar + idx * 8; }

DEVINL void store_frag(uint4* dst, const float* a, int lane) {
#pragma unroll
  for (int j = 0; j < 8; j++)
    dst[j * 32 + lane] = make_uint4(pack_bf16(a[8 * j], a[8 * j + 1]), pack_bf16(a[8 * j + 2], a[8 * j + 3]),
                                    pack_bf16(a[8 * j + 4], a[8 * j + 5]), pack_bf16(a[8 * j + 6], a[8 * j + 7]));
}

constexpr float kScale = 0.08838834764831845f * 1.4426950408889634f;
DEVINL void attention(const Ctx& c, const uint32_t (&qf)[32], int base, int t0, int tstep, int nturn, int wg, int qbar,
                      uint32_t kv_cnt, uint32_t q_cnt,
                      float (&o)[64], float& m0, float& m1, float& l0, float& l1) {
  float s[32];
  uint32_t pf[16];
  m0 = -INFINITY; m1 = -INFINITY;
  l0 = 0.f; l1 = 0.f;
#pragma unroll
  for (int i = 0; i < 64; i++) o[i] = 0.f;

#pragma unroll 1
  for (int t = t0, turn = 0; turn < nturn; t += tstep, turn++) {
    if (t >= 8) break;
    const int nk = base + 2 * t;
    mbar_wait_warp(bar_addr(c, kBarFull + nk), 0);
    const uint64_t dk = make_desc(c.sbase + (nk % kRing) * kSlot, 16, 1024);
    wgmma_fence();
    wgmma_rs_n64_init(s, qf[0], qf[1], qf[2], qf[3], dk);
#pragma unroll
    for (int j = 1; j < 8; j++)
      wgmma_rs_n64(s, qf[4 * j], qf[4 * j + 1], qf[4 * j + 2], qf[4 * j + 3], dk + (j >> 2) * 512 + (j & 3) * 2, 1);
    wgmma_commit();
    wgmma_wait<0>();
    fence_regs(s);
    if (c.lane == 0) {
      mbar_arrive(bar_addr(c, kBarEmpty + nk), kv_cnt);
      if (t == t0 && qbar >= 0) mbar_arrive(bar_addr(c, qbar), q_cnt);
    }
    if (tstep == 1) bar_sync(4 + wg, 256);
    fence_regs(s);
    uint32_t tok;
    {
      float mx0, mx1;
      {
        float a[8], b[8];
#pragma unroll
        for (int n = 0; n < 8; n++) {
          a[n] = fmaxf(s[4 * n], s[4 * n + 1]);
          b[n] = fmaxf(s[4 * n + 2], s[4 * n + 3]);
        }
#pragma unroll
        for (int w = 4; w >= 1; w >>= 1) {
#pragma unroll
          for (int n = 0; n < w; n++) {
            a[n] = fmaxf(a[n], a[n + w]);
            b[n] = fmaxf(b[n], b[n + w]);
          }
        }
        mx0 = a[0]; mx1 = b[0];
      }
      const bool grow = (mx0 - m0) * kScale > 8.f || (mx1 - m1) * kScale > 8.f;
      if (__any_sync(0xffffffffu, grow)) {
        mx0 = fmaxf(mx0, __shfl_xor_sync(0xffffffffu, mx0, 1));
        mx1 = fmaxf(mx1, __shfl_xor_sync(0xffffffffu, mx1, 1));
        mx0 = fmaxf(mx0, __shfl_xor_sync(0xffffffffu, mx0, 2));
        mx1 = fmaxf(mx1, __shfl_xor_sync(0xffffffffu, mx1, 2));
        const float n0 = fmaxf(m0, mx0), n1 = fmaxf(m1, mx1);
        const float a0 = ex2((m0 - n0) * kScale), a1 = ex2((m1 - n1) * kScale);
        m0 = n0; m1 = n1;
        l0 *= a0; l1 *= a1;
#pragma unroll
        for (int n = 0; n < 16; n++) {
          o[4 * n] *= a0; o[4 * n + 1] *= a0;
          o[4 * n + 2] *= a1; o[4 * n + 3] *= a1;
        }
      }
      const float mn0 = m0, mn1 = m1;
      const float b0 = -mn0 * kScale, b1 = -mn1 * kScale;
      float r0 = 0.f, r1 = 0.f, r2 = 0.f, r3 = 0.f;
#pragma unroll
      for (int n = 0; n < 8; n++) {
        const float p0 = ex2(fmaf(s[4 * n], kScale, b0));
        const float p1 = ex2(fmaf(s[4 * n + 1], kScale, b0));
        const float p2 = ex2(fmaf(s[4 * n + 2], kScale, b1));
        const float p3 = ex2(fmaf(s[4 * n + 3], kScale, b1));
        r0 += p0; r2 += p1;
        r1 += p2; r3 += p3;
        pf[2 * n] = pack_bf16(p0, p1);
        pf[2 * n + 1] = pack_bf16(p2, p3);
      }
      r0 += r2;
      r1 += r3;
      l0 += r0;
      l1 += r1;
      tok = (r0 < 0.f || r1 < 0.f) ? 1u : 0u;
    }
    fence_regs(pf);
    if (tstep == 1) bar_arrive((wg == 2 ? 4 : 5 + wg) + tok, 256);
    const int nv = nk + 1;
    mbar_wait_warp(bar_addr(c, kBarFull + nv), 0);
    const uint64_t dv = make_desc(c.sbase + (nv % kRing) * kSlot, 8192, 1024);
    fence_regs(o);
    fence_regs(pf);
    wgmma_fence();
#pragma unroll
    for (int j = 0; j < 4; j++)
      wgmma_rs_n128_tb(o, pf[4 * j], pf[4 * j + 1], pf[4 * j + 2], pf[4 * j + 3], dv + j * 128, 1);
    wgmma_commit();
    wgmma_wait<0>();
    fence_regs(o);
    fence_regs(pf);
    if (c.lane == 0) mbar_arrive(bar_addr(c, kBarEmpty + nv), kv_cnt);
  }
  l0 += __shfl_xor_sync(0xffffffffu, l0, 1);
  l1 += __shfl_xor_sync(0xffffffffu, l1, 1);
  l0 += __shfl_xor_sync(0xffffffffu, l0, 2);
  l1 += __shfl_xor_sync(0xffffffffu, l1, 2);
}

__constant__ unsigned short c_sched[576] = {
    512, 544, 576, 608, 640, 672, 704, 736, 768, 800, 832, 864, 896, 928, 960, 992, 32, 64, 96, 160, 192, 224, 288, 320,
    352, 416, 448, 480, 33, 65, 97, 161, 193, 225, 289, 321, 353, 417, 449, 481, 34, 66, 98, 162, 194, 226, 290, 322,
    354, 418, 450, 482, 513, 545, 577, 609, 641, 673, 705, 737, 769, 801, 833, 865, 897, 929, 961, 993, 35, 67, 99, 163,
    195, 227, 291, 323, 355, 419, 451, 483, 36, 68, 100, 164, 196, 228, 292, 324, 356, 420, 452, 484, 37, 69, 101, 165,
    197, 229, 293, 325, 357, 421, 453, 485, 514, 546, 578, 610, 642, 674, 706, 738, 770, 802, 834, 866, 898, 930, 962, 994,
    38, 70, 102, 166, 198, 230, 294, 326, 358, 422, 454, 486, 39, 71, 103, 167, 199, 231, 295, 327, 359, 423, 455, 487,
    40, 72, 104, 168, 200, 232, 296, 328, 360, 424, 456, 488, 515, 547, 579, 611, 643, 675, 707, 739, 771, 803, 835, 867,
    899, 931, 963, 995, 41, 73, 105, 169, 201, 233, 297, 329, 361, 425, 457, 489, 42, 74, 106, 170, 202, 234, 298, 330,
    362, 426, 458, 490, 43, 75, 107, 171, 203, 235, 299, 331, 363, 427, 459, 491, 516, 548, 580, 612, 644, 676, 708, 740,
    772, 804, 836, 868, 900, 932, 964, 996, 44, 76, 108, 172, 204, 236, 300, 332, 364, 428, 460, 492, 45, 77, 109, 173,
    205, 237, 301, 333, 365, 429, 461, 493, 46, 78, 110, 174, 206, 238, 302, 334, 366, 430, 462, 494, 517, 549, 581, 613,
    645, 677, 709, 741, 773, 805, 837, 869, 901, 933, 965, 997, 47, 79, 111, 175, 207, 239, 303, 335, 367, 431, 463, 495,
    16, 48, 80, 112, 144, 176, 208, 240, 272, 304, 336, 368, 400, 432, 464, 496, 17, 49, 81, 113, 145, 177, 209, 241,
    273, 305, 337, 369, 401, 433, 465, 497, 518, 550, 582, 614, 646, 678, 710, 742, 774, 806, 838, 870, 902, 934, 966, 998,
    18, 50, 82, 114, 146, 178, 210, 242, 274, 306, 338, 370, 402, 434, 466, 498, 19, 51, 83, 115, 147, 179, 211, 243,
    275, 307, 339, 371, 403, 435, 467, 499, 20, 52, 84, 116, 148, 180, 212, 244, 276, 308, 340, 372, 404, 436, 468, 500,
    519, 551, 583, 615, 647, 679, 711, 743, 775, 807, 839, 871, 903, 935, 967, 999, 21, 53, 85, 117, 149, 181, 213, 245,
    277, 309, 341, 373, 405, 437, 469, 501, 22, 54, 86, 118, 150, 182, 214, 246, 278, 310, 342, 374, 406, 438, 470, 502,
    23, 55, 87, 119, 151, 183, 215, 247, 279, 311, 343, 375, 407, 439, 471, 503, 24, 56, 88, 120, 152, 184, 216, 248,
    280, 312, 344, 376, 408, 440, 472, 504, 25, 57, 89, 121, 153, 185, 217, 249, 281, 313, 345, 377, 409, 441, 473, 505,
    26, 58, 90, 122, 154, 186, 218, 250, 282, 314, 346, 378, 410, 442, 474, 506, 27, 59, 91, 123, 155, 187, 219, 251,
    283, 315, 347, 379, 411, 443, 475, 507, 28, 60, 92, 124, 156, 188, 220, 252, 284, 316, 348, 380, 412, 444, 476, 508,
    29, 61, 93, 125, 157, 189, 221, 253, 285, 317, 349, 381, 413, 445, 477, 509, 30, 62, 94, 126, 158, 190, 222, 254,
    286, 318, 350, 382, 414, 446, 478, 510, 31, 63, 95, 127, 159, 191, 223, 255, 287, 319, 351, 383, 415, 447, 479, 511};
constexpr int kNSched = 576;
constexpr int kEnd = 0xffff;
struct Unit { int isA, b, h; };
DEVINL Unit decode_unit(int code) {
  Unit u;
  u.isA = code >> 9;
  u.b = (code >> 5) & 15;
  u.h = code & 31;
  return u;
}
DEVINL void wait_q(const Unit& u, unsigned ep1) {
  if (u.isA) wait_flag(&g_flags[(kFlagQA + u.h * 4 + (u.b >> 2)) * kFlagStride], ep1 * 4);
  else wait_flag(&g_flags[(kFlagQB + u.h * 4 + (u.b >> 2)) * kFlagStride], ep1);
}

DEVINL void store_row_bf16(uint32_t (&w)[16], __nv_bfloat16* row, int lane) {
  const bool b0 = lane & 1, b1 = lane & 2;
#pragma unroll
  for (int m = 0; m < 4; m++) {
    uint32_t a0 = w[4 * m], a1 = w[4 * m + 1], a2 = w[4 * m + 2], a3 = w[4 * m + 3], t;
    t = __shfl_xor_sync(0xffffffffu, b0 ? a0 : a1, 1); if (b0) a0 = t; else a1 = t;
    t = __shfl_xor_sync(0xffffffffu, b0 ? a2 : a3, 1); if (b0) a2 = t; else a3 = t;
    t = __shfl_xor_sync(0xffffffffu, b1 ? a0 : a2, 2); if (b1) a0 = t; else a2 = t;
    t = __shfl_xor_sync(0xffffffffu, b1 ? a1 : a3, 2); if (b1) a1 = t; else a3 = t;
    *reinterpret_cast<uint4*>(row + (4 * m + (lane & 3)) * 8) = make_uint4(a0, a1, a2, a3);
  }
}
DEVINL void store_half_row(uint32_t (&w)[8], __nv_bfloat16* row, int lane, int enable) {
  const bool b0 = lane & 1, b1 = lane & 2;
#pragma unroll
  for (int m = 0; m < 2; m++) {
    uint32_t a0 = w[4 * m], a1 = w[4 * m + 1], a2 = w[4 * m + 2], a3 = w[4 * m + 3], t;
    t = __shfl_xor_sync(0xffffffffu, b0 ? a0 : a1, 1); if (b0) a0 = t; else a1 = t;
    t = __shfl_xor_sync(0xffffffffu, b0 ? a2 : a3, 1); if (b0) a2 = t; else a3 = t;
    t = __shfl_xor_sync(0xffffffffu, b1 ? a0 : a2, 2); if (b1) a0 = t; else a2 = t;
    t = __shfl_xor_sync(0xffffffffu, b1 ? a1 : a3, 2); if (b1) a1 = t; else a3 = t;
    if (enable) *reinterpret_cast<uint4*>(row + (4 * m + (lane & 3)) * 8) = make_uint4(a0, a1, a2, a3);
  }
}
DEVINL void store_tile(const float (&o)[64], float i0, float i1, __nv_bfloat16* dst, int pitch, int lane) {
  uint32_t w[16];
#pragma unroll
  for (int n = 0; n < 16; n++) w[n] = pack_bf16(o[4 * n] * i0, o[4 * n + 1] * i0);
  store_row_bf16(w, dst, lane);
#pragma unroll
  for (int n = 0; n < 16; n++) w[n] = pack_bf16(o[4 * n + 2] * i1, o[4 * n + 3] * i1);
  store_row_bf16(w, dst + 8 * pitch, lane);
}

__global__ void __launch_bounds__(512, 1) fused_kernel(const __grid_constant__ Maps maps, __nv_bfloat16* __restrict__ out) {
  extern __shared__ uint8_t smem_raw[];
  const uint32_t sraw = smem_u32(smem_raw);
  const uint32_t sbase = (sraw + 1023u) & ~1023u;
  uint8_t* sgen = smem_raw + (sbase - sraw);
  volatile uint32_t* s_misc = reinterpret_cast<volatile uint32_t*>(sgen + kSmemMisc);
  volatile uint32_t* s_order = reinterpret_cast<volatile uint32_t*>(sgen + kSmemStats);

  const int warp_idx = __shfl_sync(0xffffffffu, threadIdx.x >> 5, 0);
  const int lane = threadIdx.x & 31;
  const int wg = warp_idx >> 2;
  const int cta = blockIdx.x;
  constexpr int nattn = kNAttn;
  const bool is_attn = cta < nattn;
  const int oproj = cta - ((int)gridDim.x - kNOproj);
  const int oX = oproj >= 16, otile = oX ? (oproj - 16) >> 1 : oproj, og = otile >> 2, oi = otile & 3;
  const int onst = oX ? 32 : 64, ono = oX ? kNOB : kNOA;

  Ctx c;
  c.sbase = sbase;
  c.warp = warp_idx & 3;
  c.lane = lane;

  const bool single = cta < 64;
  const int npair = single ? 0 : (cta < 96 ? 1 : (cta >= 100 ? 2 : 0));
  const bool has_q = single || npair > 0;
  const int nq1 = single ? 8 : 8 * npair;
  const int q1_nst = (single || !is_attn) ? 3 : 2;
  const uint32_t q1_off = is_attn ? kQOff : 0, q1_stage = single ? kQ1Stage : kQStage;
  const int qg = cta & 3;
  const int pairX = cta < 100, pairP0 = cta < 100 ? 8 + ((cta - 64) >> 2) : (cta - 100) >> 2;
  auto issue_q1 = [&](int n) {
    const uint32_t st = sbase + q1_off + (n % q1_nst) * q1_stage, fb = bar_addr(c, kBarFull + kBar1 + n);
    mbar_expect_tx(fb, q1_stage);
    uint64_t pol;
    asm volatile("createpolicy.fractional.L2::evict_first.b64 %0, 1.0;" : "=l"(pol));
    if (single) {
      tma_2d(st, &maps.xB, fb, n * 64, qg * 192);
      tma_3d_hint(st + 24576, &maps.wqB2, fb, 0, n * 64, (cta >> 2) * 2, pol);
    } else {
      tma_2d(st, pairX ? &maps.xB : &maps.xA, fb, (n & 7) * 64, qg * 192);
      tma_3d_hint(st + 24576, pairX ? &maps.wqB : &maps.wqA, fb, 0, (n & 7) * 64, (pairP0 + 8 * (n >> 3)) * 4, pol);
    }
  };
  const int code0 = single ? (((cta & 3) * 4) << 5 | (cta >> 2)) : (is_attn ? c_sched[cta - 64] : kEnd);
  auto kv_row = [&](const Unit& u, int i) { return (u.b * (u.isA ? 8 : 32) + u.h) * 512 + (i >> 1) * 64; };
  auto issue_kv = [&](const Unit& u, int i, int n, uint64_t pol) {
    const CUtensorMap* map = u.isA ? ((i & 1) ? &maps.vA : &maps.kA) : ((i & 1) ? &maps.vB : &maps.kB);
    mbar_expect_tx(bar_addr(c, kBarFull + n), kSlot);
    tma_3d_hint(sbase + (n % kRing) * kSlot, map, bar_addr(c, kBarFull + n), 0, kv_row(u, i), 0, pol);
  };
  if (warp_idx == 13 && lane == 0) {
    if (has_q) for (int k = 0; k < 2; k++) mbar_init(bar_addr(c, kBarFull + kBar1 + k), 1);
    if (is_attn) for (int k = 0; k < kEarlyKV; k++) mbar_init(bar_addr(c, kBarFull + k), 1);
    asm volatile("fence.mbarrier_init.release.cluster;" ::: "memory");
    if (has_q) for (int k = 0; k < 2; k++) issue_q1(k);
    if (is_attn) {
      uint64_t pol;
      asm volatile("createpolicy.fractional.L2::evict_first.b64 %0, 1.0;" : "=l"(pol));
      const Unit u0 = decode_unit(code0);
      for (int k = 0; k < kEarlyKV; k++) issue_kv(u0, k, k, pol);
    }
  }
  {
    static_assert(kNumBars <= 512, "one barrier per thread");
    const int t = threadIdx.x;
    int cnt = 1;
    cnt = (t < 64 && !is_attn) ? 65 : cnt;
    cnt = (t >= kBarEmpty && t < kBarEpoch) ? 12 : cnt;
    cnt = (t == kBarP1Done || (t >= kBarQStored && t < kBarGo) || t >= kBarSig) ? 12 : cnt;
    const bool early = (has_q && t >= kBar1 && t < kBar1 + 2) || (is_attn && t < kEarlyKV);
    if (t < kNumBars && !early) mbar_init(bar_addr(c, t), cnt);
    if (t == 0) s_misc[1] = code0;
  }
  asm volatile("fence.mbarrier_init.release.cluster;" ::: "memory");
  __syncthreads();
  asm volatile("barrier.cluster.arrive.release.aligned;" ::: "memory");

  if (wg == 3) {
    asm volatile("setmaxnreg.dec.sync.aligned.u32 32;");
    auto o_loader = [&](int w) {
      const int X = oX, g = og;
      const int tt = w * 32 + lane, r8 = tt >> 3, ch = tt & 7;
      const uint8_t* src0 = reinterpret_cast<const uint8_t*>(g_Q) + (size_t)((X * 16 + g * 4) * 32) * 12288 + r8 * 256 + ch * 16;
      const uint32_t dst0 = sbase + r8 * 128 + ((ch ^ r8) << 4);
      if (has_q) mbar_wait(bar_addr(c, kBarP1Done), 0);
      int head0 = 0;
#pragma unroll 1
      for (int n = 0; n < onst; n++) {
        const int sub = X ? n & 1 : n & 7;
        if (sub == 0) {
          const int q = X ? n >> 1 : n >> 3;
          mbar_wait(bar_addr(c, kBarFull + 96 + q), 0);
          head0 = s_order[q] * (X ? 1 : 4);
        }
        if (n >= ono) mbar_wait(bar_addr(c, kBarEmpty + n - ono), 0);
        const uint8_t* src = src0 + (size_t)(head0 + (sub >> 1)) * 12288 + (sub & 1) * 128;
        const uint32_t dst = dst0 + (n % ono) * kOStage;
#pragma unroll
        for (int j = 0; j < 24; j++)
          asm volatile("cp.async.cg.shared.global [%0], [%1], 16;" ::"r"(dst + j * 1024),
                       "l"(src + (size_t)(j / 6) * (32 * 12288) + (j % 6) * 2048) : "memory");
        asm volatile("cp.async.mbarrier.arrive.noinc.shared::cta.b64 [%0];" ::"r"(bar_addr(c, kBarFull + n)) : "memory");
      }
      asm volatile("cp.async.wait_all;" ::: "memory");
    };
    if (warp_idx == 12) {
      if (lane == 0 && is_attn) {
        uint64_t pol;
        asm volatile("createpolicy.fractional.L2::evict_first.b64 %0, 1.0;" : "=l"(pol));
        mbar_wait(bar_addr(c, kBarEpoch), 0);
        const unsigned ep1 = s_misc[0];
        mbar_wait(bar_addr(c, kBarP1Done), 0);
        int n = 0;
#pragma unroll 1
        for (int k = 0; k <= kMaxUnits; k++) {
          if (k > 0) mbar_wait(bar_addr(c, kBarUnit + k), 0);
          const int s = s_misc[1 + k];
          if (s == kEnd) break;
          const Unit u = decode_unit(s);
          const int nq = u.isA ? 3 : 1;
          if (k == 0) {
            n = kPre;
#pragma unroll 1
            for (; n < kRing; n++) issue_kv(u, n, n, pol);
            if (cta >= 64) {
              wait_q(u, ep1);
              fence_proxy_async_global();
            }
          } else {
            fence_proxy_async_global();
          }
#pragma unroll 1
          for (int w = 0; w < ((k == 0 && cta < 64) ? 0 : nq); w++) {
            const int grp0 = u.isA ? (u.b * 32 + u.h * 4) * 3 + 4 * w : ((16 + u.b) * 32 + u.h) * 3;
            const uint32_t bytes = u.isA ? 16384u : 12288u;
            uint32_t fb, dst;
            if (k == 0) {
              fb = bar_addr(c, kBarQ0 + w);
              dst = sbase + kMergeOff + w * kSlot;
            } else {
              mbar_wait(bar_addr(c, kBarEmpty + n - kRing), 0);
              fb = bar_addr(c, kBarFull + n);
              dst = sbase + (n % kRing) * kSlot;
              n++;
            }
            mbar_expect_tx(fb, bytes);
            bulk_1d(dst, g_Q + (size_t)grp0 * 256, bytes, fb);
          }
#pragma unroll 1
          for (int i = k == 0 ? kRing : 0; i < 16; i++, n++) {
            mbar_wait(bar_addr(c, kBarEmpty + n - kRing), 0);
            issue_kv(u, i, n, pol);
            if (i == (k == 0 ? kRing : 8)) mbar_arrive(bar_addr(c, kBarGo + k), 1);
          }
        }
      } else if (oproj >= 0) {
        const int X = oX, g = og;
        mbar_wait(bar_addr(c, kBarEpoch), 0);
        const unsigned target = s_misc[0] * 4;
        const unsigned* fp = &g_flags[(X == 0 ? kFlagOA + g * 8 + min(lane, 7)
                                              : kFlagOB + g * 32 + 2 * min(lane, 15) + (oproj & 1)) * kFlagStride];
        unsigned pending = X ? 0xffffu : 0xffu;
        int q = 0;
#pragma unroll 1
        for (int it = 0; pending != 0 && it < (1 << 22); it++) {
          const bool rdy = (int)(ld_acquire(fp) - target) >= 0;
          unsigned ready = __ballot_sync(0xffffffffu, rdy) & pending;
          pending &= ~ready;
          if (lane == 0) {
            while (ready) {
              const int st = __ffs(ready) - 1;
              ready &= ready - 1;
              s_order[q] = X ? 2 * st + (oproj & 1) : st;
              mbar_arrive(bar_addr(c, kBarFull + 96 + q), 1);
              q++;
            }
          }
          q = __shfl_sync(0xffffffffu, q, 0);
        }
      }
    } else if (warp_idx == 13) {
      if (lane == 0) {
        uint64_t pol;
        asm volatile("createpolicy.fractional.L2::evict_first.b64 %0, 1.0;" : "=l"(pol));
        const Unit u0 = decode_unit(s_misc[1]);
        int kvn = kEarlyKV;
        if (has_q) {
#pragma unroll 1
          for (int n = 2; n < nq1; n++) {
            if (n >= q1_nst) mbar_wait(bar_addr(c, kBarEmpty + kBar1 + n - q1_nst), 0);
            issue_q1(n);
            if (is_attn && kvn < kPre) { issue_kv(u0, kvn, kvn, pol); kvn++; }
          }
        }
        if (is_attn) {
          while (kvn < kPre) { issue_kv(u0, kvn, kvn, pol); kvn++; }
          mbar_wait(bar_addr(c, kBarEpoch), 0);
          const unsigned ep1 = s_misc[0];
#pragma unroll 1
          for (int k = 1; k <= kMaxUnits; k++) {
            mbar_wait(bar_addr(c, kBarGo + k - 1), 0);
            unsigned s = kEnd;
            if (k < kMaxUnits) {
              const unsigned pos = (nattn - 64) + (k == 1 ? cta : nattn + atomicAdd(&g_next, 1u));
              if (pos < kNSched) s = c_sched[pos];
            }
            if (s != kEnd) wait_q(decode_unit(s), ep1);
            s_misc[1 + k] = s;
            mbar_arrive(bar_addr(c, kBarUnit + k), 1);
            if (s == kEnd) break;
          }
          if (atomicAdd(&g_sched_done, 1u) == nattn - 1) {
            g_next = 0;
            g_sched_done = 0;
          }
        } else if (oproj >= 0) {
          const int X = oX, i = oi;
          if (has_q) mbar_wait(bar_addr(c, kBarP1Done), 0);
          int krow = 0;
#pragma unroll 1
          for (int n = 0; n < onst; n++) {
            const uint32_t fb = bar_addr(c, kBarFull + n);
            const int sub = X ? n & 1 : n & 7;
            if (sub == 0) {
              const int q = X ? n >> 1 : n >> 3;
              mbar_wait(bar_addr(c, kBarFull + 96 + q), 0);
              krow = s_order[q] * (X ? 128 : 512);
            }
            if (n >= ono) mbar_wait(bar_addr(c, kBarEmpty + n - ono), 0);
            mbar_expect_tx(fb, 16384);
            tma_3d_hint(sbase + (n % ono) * kOStage + 24576, X ? &maps.woB : &maps.woA, fb, 0, krow + sub * 64, i * 2, pol);
          }
        }
      }
    } else if (warp_idx == 14) {
      if (lane == 0) {
        if (single) {
          mbar_wait(bar_addr(c, kBarQStored), 0);
          asm volatile("fence.acq_rel.gpu;" ::: "memory");
          asm volatile("red.relaxed.gpu.global.add.u32 [%0], %1;" ::"l"(&g_flags[(kFlagQB + (cta >> 2) * 4 + qg) * kFlagStride]), "r"(1u) : "memory");
        }
#pragma unroll 1
        for (int r = 0; r < npair; r++) {
          const int P = pairP0 + 8 * r;
          mbar_wait(bar_addr(c, kBarQStored + r), 0);
          asm volatile("fence.acq_rel.gpu;" ::: "memory");
          if (pairX) {
            asm volatile("red.relaxed.gpu.global.add.u32 [%0], %1;" ::"l"(&g_flags[(kFlagQB + 2 * P * 4 + qg) * kFlagStride]), "r"(1u) : "memory");
            asm volatile("red.relaxed.gpu.global.add.u32 [%0], %1;" ::"l"(&g_flags[(kFlagQB + (2 * P + 1) * 4 + qg) * kFlagStride]), "r"(1u) : "memory");
          } else {
            asm volatile("red.relaxed.gpu.global.add.u32 [%0], %1;" ::"l"(&g_flags[(kFlagQA + (P >> 1) * 4 + qg) * kFlagStride]), "r"(2u) : "memory");
          }
        }
      }
      __syncwarp();
      if (oproj >= 0) {
        o_loader(0);
      } else if (lane == 0 && is_attn) {
#pragma unroll 1
        for (int k = 0; k <= kMaxUnits; k++) {
          if (k > 0) mbar_wait(bar_addr(c, kBarUnit + k), 0);
          const int s = s_misc[1 + k];
          if (s == kEnd) break;
          const Unit u = decode_unit(s);
          const int f = u.isA ? kFlagOA + (u.b >> 2) * 8 + u.h : kFlagOB + (u.b >> 2) * 32 + u.h;
          mbar_wait(bar_addr(c, kBarSig + k), 0);
          asm volatile("fence.acq_rel.gpu;" ::: "memory");
          asm volatile("red.relaxed.gpu.global.add.u32 [%0], %1;" ::"l"(&g_flags[f * kFlagStride]), "r"(1u) : "memory");
        }
      }
    } else {
      if (lane == 0) {
        unsigned e;
        asm volatile("ld.relaxed.gpu.global.u32 %0, [%1];" : "=r"(e) : "l"(&g_epoch) : "memory");
        s_misc[0] = e + 1;
        mbar_arrive(bar_addr(c, kBarEpoch), 1);
        unsigned old = atomicAdd(&g_started, 1u);
        if (old == gridDim.x - 1) {
          g_started = 0;
          __threadfence();
          asm volatile("st.relaxed.gpu.global.u32 [%0], %1;" ::"l"(&g_epoch), "r"(e + 1) : "memory");
        }
      }
      __syncwarp();
      if (oproj >= 0) o_loader(1);
    }
  } else {
    asm volatile("setmaxnreg.inc.sync.aligned.u32 160;");
    if (single) {
      float acc[64];
#pragma unroll 1
      for (int k = 0; k < 8; k++) {
        const uint32_t st = sbase + kQOff + (k % 3) * kQ1Stage;
        mbar_wait_warp(bar_addr(c, kBarFull + kBar1 + k), 0);
        const uint64_t da = make_desc(st + wg * 8192, 16, 1024);
        const uint64_t db = make_desc(st + 24576, 8192, 1024);
        fence_regs(acc);
        wgmma_fence();
#pragma unroll
        for (int j = 0; j < 4; j++) wgmma_ss_n128_tb(acc, da + j * 2, db + j * 128, (k | j) != 0);
        wgmma_commit();
        wgmma_wait<0>();
        if (lane == 0) mbar_arrive(bar_addr(c, kBarEmpty + kBar1 + k), 1);
      }
      fence_regs(acc);
      const int G = 4 * wg + c.warp;
      if (lane == 0) mbar_arrive(bar_addr(c, kBarP1Done), 1);
      bar_sync(1, 384);
      if (G < 3) store_frag(reinterpret_cast<uint4*>(sgen + kMergeOff) + G * 256, acc, lane);
      bar_sync(2, 384);
      store_frag(g_Q + (size_t)(((16 + qg * 4 + G / 3) * 32 + (cta >> 2)) * 3 + G % 3) * 256, acc, lane);
      __syncwarp();
      if (lane == 0) mbar_arrive(bar_addr(c, kBarQStored), 1);
    } else if (npair > 0) {
      float acc[2][64];
#pragma unroll 1
      for (int r = 0; r < npair; r++) {
#pragma unroll 1
        for (int k = 0; k < 8; k++) {
          const int n = r * 8 + k;
          const uint32_t st = sbase + q1_off + (n % q1_nst) * kQStage;
          mbar_wait_warp(bar_addr(c, kBarFull + kBar1 + n), 0);
          const uint64_t da = make_desc(st + wg * 8192, 16, 1024);
          const uint64_t db = make_desc(st + 24576, 8192, 1024);
          fence_regs(acc[0]);
          fence_regs(acc[1]);
          wgmma_fence();
#pragma unroll
          for (int j = 0; j < 4; j++) {
            wgmma_ss_n128_tb(acc[0], da + j * 2, db + j * 128, (k | j) != 0);
            wgmma_ss_n128_tb(acc[1], da + j * 2, db + 1024 + j * 128, (k | j) != 0);
          }
          wgmma_commit();
          wgmma_wait<0>();
          if (lane == 0) mbar_arrive(bar_addr(c, kBarEmpty + kBar1 + n), 1);
        }
        fence_regs(acc[0]);
        fence_regs(acc[1]);
        if (r == npair - 1 && lane == 0) mbar_arrive(bar_addr(c, kBarP1Done), 1);
        const int G = 4 * wg + c.warp;
        uint4* dst = g_Q + (size_t)(((pairX * 16 + qg * 4 + G / 3) * 32 + 2 * (pairP0 + 8 * r)) * 3 + G % 3) * 256;
        store_frag(dst, acc[0], lane);
        store_frag(dst + 3 * 256, acc[1], lane);
        __syncwarp();
        if (lane == 0) mbar_arrive(bar_addr(c, kBarQStored + r), 1);
      }
    }

    if (is_attn) {
      if (wg == 2) bar_arrive(4, 256);
      int base = 0;
      float2* stats = reinterpret_cast<float2*>(sgen + kSmemStats);
#pragma unroll 1
      for (int k = 0; k <= kMaxUnits; k++) {
        if (k > 0) mbar_wait_warp(bar_addr(c, kBarUnit + k), 0);
        const int s = __shfl_sync(0xffffffffu, (int)s_misc[1 + k], 0);
        if (s == kEnd) break;
        const bool isA = s >> 9;
        const int nq = k == 0 ? 0 : (isA ? 3 : 1);
        uint32_t qf[32];
        {
          const int w = isA ? wg : 0;
          const int n = base + w;
          if (k > 0 || cta >= 64) mbar_wait_warp(bar_addr(c, k == 0 ? kBarQ0 + w : kBarFull + n), 0);
          const uint4* q = reinterpret_cast<const uint4*>(sgen + (k == 0 ? kMergeOff + w * kSlot : (n % kRing) * kSlot)) +
                           (isA || c.warp < 3 ? c.warp : 2) * 256 + lane;
#pragma unroll
          for (int j = 0; j < 8; j++) {
            const uint4 v = q[j * 32];
            qf[4 * j] = v.x; qf[4 * j + 1] = v.y; qf[4 * j + 2] = v.z; qf[4 * j + 3] = v.w;
          }
        }
        float o[64];
        float m0, m1, l0, l1;
        attention(c, qf, base + nq, isA ? 0 : wg, isA ? 1 : 3, isA ? 8 : 3, wg, k > 0 ? kBarEmpty + base + (isA ? wg : 0) : -1,
                  isA ? 1u : 3u, isA ? 3u : 1u, o, m0, m1, l0, l1);
        int s2 = s;
        asm volatile("" : "+r"(s2));
        const Unit u = decode_unit(s2);
        if (isA) {
          const int G = 4 * wg + c.warp;
          store_tile(o, rcp_approx(l0), rcp_approx(l1),
                     reinterpret_cast<__nv_bfloat16*>(g_Q) + (size_t)(u.b * 32 + u.h * 4 + G / 3) * 6144 + ((G % 3) * 16 + (lane >> 2)) * 128,
                     128, lane);
          __syncwarp();
          if (lane == 0) mbar_arrive(bar_addr(c, kBarSig + k), 1);
        } else {
          const int r0 = c.warp * 16 + (lane >> 2);
          if (c.warp < 3 && (lane & 3) == 0) {
            stats[wg * 48 + r0] = make_float2(m0, l0);
            stats[wg * 48 + r0 + 8] = make_float2(m1, l1);
          }
          bar_sync(1, 384);
          const int fin = k % 3;
          if (c.warp < 3) {
            const float2 xa = stats[r0], xb = stats[48 + r0], xc = stats[96 + r0];
            const float2 ya = stats[r0 + 8], yb = stats[48 + r0 + 8], yc = stats[96 + r0 + 8];
            const float mx = fmaxf(xa.x, fmaxf(xb.x, xc.x)), my = fmaxf(ya.x, fmaxf(yb.x, yc.x));
            const float lx = xa.y * ex2((xa.x - mx) * kScale) + xb.y * ex2((xb.x - mx) * kScale) + xc.y * ex2((xc.x - mx) * kScale);
            const float ly = ya.y * ex2((ya.x - my) * kScale) + yb.y * ex2((yb.x - my) * kScale) + yc.y * ex2((yc.x - my) * kScale);
            const float f0 = ex2((m0 - mx) * kScale) * rcp_approx(lx), f1 = ex2((m1 - my) * kScale) * rcp_approx(ly);
#pragma unroll
            for (int n = 0; n < 16; n++) {
              o[4 * n] *= f0; o[4 * n + 1] *= f0;
              o[4 * n + 2] *= f1; o[4 * n + 3] *= f1;
            }
            if (wg != fin) {
              float4* dst = reinterpret_cast<float4*>(sgen + kMergeOff) + ((wg + 3 - fin) % 3 - 1) * (16 * 96) + c.warp * 32 + lane;
#pragma unroll
              for (int n = 0; n < 16; n++) dst[n * 96] = make_float4(o[4 * n], o[4 * n + 1], o[4 * n + 2], o[4 * n + 3]);
            }
          }
          bar_sync(2, 384);
          if (wg == fin && c.warp < 3) {
            const float4* src = reinterpret_cast<const float4*>(sgen + kMergeOff) + c.warp * 32 + lane;
#pragma unroll
            for (int n = 0; n < 16; n++) {
              const float4 x = src[n * 96], y = src[16 * 96 + n * 96];
              o[4 * n] += x.x + y.x; o[4 * n + 1] += x.y + y.y;
              o[4 * n + 2] += x.z + y.z; o[4 * n + 3] += x.w + y.w;
            }
            store_tile(o, 1.f, 1.f, reinterpret_cast<__nv_bfloat16*>(g_Q) + (size_t)((16 + u.b) * 32 + u.h) * 6144 + r0 * 128, 128, lane);
            __syncwarp();
            if (lane == 0) mbar_arrive(bar_addr(c, kBarSig + k), 4);
          }
        }
        base += 16 + nq;
      }
    } else if (oproj >= 0) {
      float acc[64];
#pragma unroll
      for (int i = 0; i < 64; i++) acc[i] = 0.f;
      if (oX) asm volatile("barrier.cluster.wait.acquire.aligned;" ::: "memory");
      const int tid = threadIdx.x;
#pragma unroll 1
      for (int pass = 0; pass < 2; pass++) {
#pragma unroll 1
        for (int n = 0; n < (pass ? onst : 0); n++) {
          const int slot = n % ono;
          const uint32_t st = sbase + slot * kOStage;
          mbar_wait_warp(bar_addr(c, kBarFull + n), 0);
          asm volatile("fence.proxy.async.shared::cta;" ::: "memory");
          const uint64_t da = make_desc(st + wg * 8192, 16, 1024);
          const uint64_t db = make_desc(st + 24576, 8192, 1024);
          fence_regs(acc);
          wgmma_fence();
#pragma unroll
          for (int j = 0; j < 4; j++) wgmma_ss_n128_tb(acc, da + j * 2, db + j * 128, (n | j) != 0);
          wgmma_commit();
          wgmma_wait<0>();
          if (lane == 0) mbar_arrive(bar_addr(c, kBarEmpty + n), 1);
        }
        fence_regs(acc);
        __nv_bfloat16* orow = out + (size_t)(og * 192 + wg * 64 + c.warp * 16 + (lane >> 2)) * 1024 + oX * 512 + oi * 128;
        if (oX) {
          const int r = cta & 1, peer = pass ? r ^ 1 : r;
          const uint32_t rb = kBarRecv + (pass ^ 1);
          const uint32_t dst = mapa(sbase + kRecvOff, peer) + tid * 16;
          if (r == 0) {
#pragma unroll
            for (int n = 0; n < 8; n++)
              asm volatile("st.shared::cluster.v4.f32 [%0], {%1, %2, %3, %4};" ::"r"(dst + n * 6144), "f"(acc[32 + 4 * n]),
                           "f"(acc[33 + 4 * n]), "f"(acc[34 + 4 * n]), "f"(acc[35 + 4 * n]) : "memory");
          } else {
#pragma unroll
            for (int n = 0; n < 8; n++)
              asm volatile("st.shared::cluster.v4.f32 [%0], {%1, %2, %3, %4};" ::"r"(dst + n * 6144), "f"(acc[4 * n]),
                           "f"(acc[4 * n + 1]), "f"(acc[4 * n + 2]), "f"(acc[4 * n + 3]) : "memory");
          }
          __syncwarp();
          if (lane == 0) mbar_arrive_remote(mapa(bar_addr(c, rb), peer));
          asm volatile(
              "{\n.reg .pred p;\n.reg .u32 n;\nmov.u32 n, 0;\n"
              "RW_LOOP:\n"
              "mbarrier.try_wait.parity.acquire.cluster.shared::cta.b64 p, [%0], 0;\n"
              "@p bra RW_DONE;\n"
              "add.u32 n, n, 1;\nsetp.lt.u32 p, n, 0x100000;\n@p bra RW_LOOP;\n"
              "RW_DONE:\n}\n" ::"r"(bar_addr(c, rb)) : "memory");
          __syncwarp();
          const float4* src = reinterpret_cast<const float4*>(sgen + kRecvOff) + tid;
          uint32_t w0[8], w1[8];
#pragma unroll
          for (int n = 0; n < 8; n++) {
            const float4 x = src[n * 384];
            const float a0 = (r ? acc[32 + 4 * n] : acc[4 * n]) + x.x, a1 = (r ? acc[33 + 4 * n] : acc[4 * n + 1]) + x.y;
            const float a2 = (r ? acc[34 + 4 * n] : acc[4 * n + 2]) + x.z, a3 = (r ? acc[35 + 4 * n] : acc[4 * n + 3]) + x.w;
            w0[n] = pack_bf16(a0, a1);
            w1[n] = pack_bf16(a2, a3);
          }
          store_half_row(w0, orow + r * 64, lane, pass);
          store_half_row(w1, orow + 8 * 1024 + r * 64, lane, pass);
        } else if (pass) {
          store_tile(acc, 1.f, 1.f, orow, 1024, lane);
        }
      }
    }
  }
}

typedef CUresult (*EncodeFn)(CUtensorMap*, CUtensorMapDataType, cuuint32_t, void*, const cuuint64_t*,
                             const cuuint64_t*, const cuuint32_t*, const cuuint32_t*, CUtensorMapInterleave,
                             CUtensorMapSwizzle, CUtensorMapL2promotion, CUtensorMapFloatOOBfill);

static bool make_map_2d(EncodeFn enc, CUtensorMap* m, const void* ptr, uint64_t cols, uint64_t rows,
                        uint32_t box_rows) {
  cuuint64_t dims[2] = {cols, rows};
  cuuint64_t strides[1] = {cols * 2};
  cuuint32_t box[2] = {64, box_rows};
  cuuint32_t es[2] = {1, 1};
  return enc(m, CU_TENSOR_MAP_DATA_TYPE_BFLOAT16, 2, const_cast<void*>(ptr), dims, strides, box, es,
             CU_TENSOR_MAP_INTERLEAVE_NONE, CU_TENSOR_MAP_SWIZZLE_128B, CU_TENSOR_MAP_L2_PROMOTION_L2_128B,
             CU_TENSOR_MAP_FLOAT_OOB_FILL_NONE) == CUDA_SUCCESS;
}
static bool make_map_3d(EncodeFn enc, CUtensorMap* m, const void* ptr, uint64_t cols, uint64_t rows, uint32_t nblk) {
  cuuint64_t dims[3] = {64, rows, cols / 64};
  cuuint64_t strides[2] = {cols * 2, 128};
  cuuint32_t box[3] = {64, 64, nblk};
  cuuint32_t es[3] = {1, 1, 1};
  return enc(m, CU_TENSOR_MAP_DATA_TYPE_BFLOAT16, 3, const_cast<void*>(ptr), dims, strides, box, es,
             CU_TENSOR_MAP_INTERLEAVE_NONE, CU_TENSOR_MAP_SWIZZLE_128B, CU_TENSOR_MAP_L2_PROMOTION_L2_128B,
             CU_TENSOR_MAP_FLOAT_OOB_FILL_NONE) == CUDA_SUCCESS;
}

__global__ void fb_gemm(const __nv_bfloat16* A, const __nv_bfloat16* B, __nv_bfloat16* C, int N, int K, int ldc) {
  const int n = blockIdx.x * blockDim.x + threadIdx.x, m = blockIdx.y;
  if (n >= N) return;
  float acc = 0.f;
  for (int k = 0; k < K; k++) acc += __bfloat162float(A[(size_t)m * K + k]) * __bfloat162float(B[(size_t)k * N + n]);
  C[(size_t)m * ldc + n] = __float2bfloat16(acc);
}
__global__ void fb_attn(__nv_bfloat16* q, const __nv_bfloat16* k, const __nv_bfloat16* v, int hkv) {
  __shared__ float p[512], red[128], qs[128];
  const int b = blockIdx.z, h = blockIdx.y, r = blockIdx.x, t = threadIdx.x, hk = h / (32 / hkv);
  __nv_bfloat16* qp = q + (size_t)(b * 48 + r) * 4096 + h * 128;
  const __nv_bfloat16* kp = k + (size_t)(b * hkv + hk) * 512 * 128;
  const __nv_bfloat16* vp = v + (size_t)(b * hkv + hk) * 512 * 128;
  qs[t] = __bfloat162float(qp[t]);
  __syncthreads();
  float mx = -INFINITY;
  for (int j = t; j < 512; j += 128) {
    float s = 0.f;
    for (int d = 0; d < 128; d++) s += qs[d] * __bfloat162float(kp[j * 128 + d]);
    s *= 0.08838834764831845f;
    p[j] = s;
    mx = fmaxf(mx, s);
  }
  red[t] = mx;
  __syncthreads();
  for (int o = 64; o > 0; o >>= 1) { if (t < o) red[t] = fmaxf(red[t], red[t + o]); __syncthreads(); }
  mx = red[0];
  __syncthreads();
  float sum = 0.f;
  for (int j = t; j < 512; j += 128) { const float e = expf(p[j] - mx); p[j] = e; sum += e; }
  red[t] = sum;
  __syncthreads();
  for (int o = 64; o > 0; o >>= 1) { if (t < o) red[t] += red[t + o]; __syncthreads(); }
  float acc = 0.f;
  for (int j = 0; j < 512; j++) acc += p[j] * __bfloat162float(vp[j * 128 + t]);
  qp[t] = __float2bfloat16(acc / red[0]);
}

}

extern "C" void kernel_launch(void* const* d_in, const int* in_sizes, int n_in, void* d_out, int out_size) {
  using namespace fk;
  (void)in_sizes; (void)n_in; (void)out_size;
  typedef const __nv_bfloat16* cbf;
  static EncodeFn enc = nullptr;
  static void* q_ptr = nullptr;
  static int fast = -1;
  constexpr int kGrid = kNAttn + kNOproj;
  cudaLaunchConfig_t cfg = {};
  cfg.gridDim = dim3(kGrid);
  cfg.blockDim = dim3(512);
  cfg.dynamicSmemBytes = kSmemTotal;
  cfg.stream = cudaStreamPerThread;
  cudaLaunchAttribute attr[1];
  attr[0].id = cudaLaunchAttributeClusterDimension;
  attr[0].val.clusterDim.x = 2; attr[0].val.clusterDim.y = 1; attr[0].val.clusterDim.z = 1;
  cfg.attrs = attr;
  cfg.numAttrs = 1;
  if (fast < 0) {
    void* fn = nullptr;
    cudaDriverEntryPointQueryResult qres;
    cudaGetDriverEntryPoint("cuTensorMapEncodeTiled", &fn, cudaEnableDefault, &qres);
    enc = (EncodeFn)fn;
    cudaGetSymbolAddress(&q_ptr, g_Q);
    int nclusters = 0;
    const bool attr_ok =
        cudaFuncSetAttribute(fused_kernel, cudaFuncAttributeMaxDynamicSharedMemorySize, kSmemTotal) == cudaSuccess;
    fast = enc != nullptr && attr_ok && cudaOccupancyMaxActiveClusters(&nclusters, fused_kernel, &cfg) == cudaSuccess &&
           nclusters * 2 >= kGrid;
    (void)cudaGetLastError();
  }
  Maps maps;
  bool ok = fast == 1;
  if (ok) {
    ok &= make_map_2d(enc, &maps.xA, d_in[0], 512, 768, 192);
    ok &= make_map_3d(enc, &maps.kA, d_in[1], 128, 16 * 8 * 512, 2);
    ok &= make_map_3d(enc, &maps.vA, d_in[2], 128, 16 * 8 * 512, 2);
    ok &= make_map_3d(enc, &maps.wqA, d_in[3], 4096, 512, 4);
    ok &= make_map_3d(enc, &maps.woA, d_in[4], 512, 4096, 2);
    ok &= make_map_2d(enc, &maps.xB, d_in[5], 512, 768, 192);
    ok &= make_map_3d(enc, &maps.kB, d_in[6], 128, 16 * 32 * 512, 2);
    ok &= make_map_3d(enc, &maps.vB, d_in[7], 128, 16 * 32 * 512, 2);
    ok &= make_map_3d(enc, &maps.wqB, d_in[8], 4096, 512, 4);
    ok &= make_map_3d(enc, &maps.woB, d_in[9], 512, 4096, 2);
      ok &= make_map_3d(enc, &maps.wqB2, d_in[8], 4096, 512, 2);
  }
  if (ok) {
    cudaLaunchKernelEx(&cfg, fused_kernel, maps, (__nv_bfloat16*)d_out);
    return;
  }
  __nv_bfloat16* q = (__nv_bfloat16*)q_ptr;
  for (int br = 0; br < 2; br++) {
    fb_gemm<<<dim3(16, 768), 256, 0, cudaStreamPerThread>>>((cbf)d_in[br * 5], (cbf)d_in[br * 5 + 3], q, 4096, 512, 4096);
    fb_attn<<<dim3(48, 32, 16), 128, 0, cudaStreamPerThread>>>(q, (cbf)d_in[br * 5 + 1], (cbf)d_in[br * 5 + 2], br ? 32 : 8);
    fb_gemm<<<dim3(2, 768), 256, 0, cudaStreamPerThread>>>(q, (cbf)d_in[br * 5 + 4], (__nv_bfloat16*)d_out + br * 512, 512,
                                                          4096, 1024);
  }
}
```
